```python
import torch

def _softmax(x, axis=-1):
    return torch.softmax(x, dim=axis)
def _gelu(x):
    return torch.nn.functional.gelu(x, approximate="tanh")
def _silu(x):
    return torch.nn.functional.silu(x)
def _sigmoid(x):
    return torch.sigmoid(x)
def _layernorm(x, axis=-1, eps=1e-5):
    m = x.mean(dim=axis, keepdim=True)
    v = x.var(dim=axis, keepdim=True, unbiased=False)
    return (x - m) / torch.sqrt(v + eps)
def _scatter_add(tgt, idx, src, axis=0):
    return tgt.clone().index_add_(axis, idx, src)
def _segment_sum(src, seg, n):
    out = torch.zeros((n,) + src.shape[1:], dtype=src.dtype)
    return out.index_add_(0, seg, src)
def _pad(x, pw):
    flat = tuple(v for pair in reversed(pw) for v in pair)
    return torch.nn.functional.pad(x, flat)

kernel_name = 'interleave_layers__mha_block__dense_activation_silu__prompt'

def setup_inputs():

    _w = (lambda a: (lambda t: t.to(torch.bfloat16) if t.is_floating_point() else t)(torch.as_tensor(a)))
    def _A_setup():
        B, S, D, H = 1, 2048, 640, 32
        return {
            "x": _w((lambda *s: torch.randn(*s, dtype=torch.bfloat16) * 0.05)(B, S, D)),
            "wqkv": _w((lambda *s: torch.randn(*s, dtype=torch.bfloat16) * 0.05)(D, 3 * D)),
            "wo": _w((lambda *s: torch.randn(*s, dtype=torch.bfloat16) * 0.05)(D, D)),
        }
    _A_in = _A_setup()

    def _B_setup():
        B, S, D, F = 1, 2048, 640, 1728
        return {
            "x": _w((lambda *s: torch.randn(*s, dtype=torch.bfloat16) * 0.05)(B, S, D)),
            "w1": _w((lambda *s: torch.randn(*s, dtype=torch.bfloat16) * 0.8)(D, F) * (D ** -0.5)),
            "w2": _w((lambda *s: torch.randn(*s, dtype=torch.bfloat16) * 0.8)(F, D) * (F ** -0.5)),
        }
    _B_in = _B_setup()

    return {
        "A_x": _A_in["x"],
        "A_wqkv": _A_in["wqkv"],
        "A_wo": _A_in["wo"],
        "B_x": _B_in["x"],
        "B_w1": _B_in["w1"],
        "B_w2": _B_in["w2"],
    }

def reference(A_x, A_wqkv, A_wo, B_x, B_w1, B_w2):
    def _A_ref(x, wqkv, wo):
        B, S, D = x.shape
        H = 32
        Dh = D // H
        qkv = (lambda x, *d: x.permute(*d))((x @ wqkv).reshape(B, S, 3, H, Dh), 2, 0, 3, 1, 4)
        q, k, v = qkv[0], qkv[1], qkv[2]
        scores = torch.einsum("bhqd,bhkd->bhqk", q, k) * (Dh ** -0.5)
        p = _softmax(scores, axis=-1)
        o = torch.einsum("bhqk,bhkd->bhqd", p, v)
        return (lambda x, *d: x.permute(*d))(o, 0, 2, 1, 3).reshape(B, S, D) @ wo

    def _B_ref(x, w1, w2):
        h = torch.einsum("bsd,df->bsf", x, w1)
        h = _silu(h)
        out = torch.einsum("bsf,fd->bsd", h, w2)
        return out

    x = A_x
    x = x + _A_ref(_layernorm(x, axis=-1), A_wqkv, A_wo)
    x = x + _B_ref(_layernorm(x, axis=-1), B_w1, B_w2)
    x = x + _A_ref(_layernorm(x, axis=-1), A_wqkv, A_wo)
    x = x + _B_ref(_layernorm(x, axis=-1), B_w1, B_w2)
    return x
```

```cpp
#include <cuda.h>
#include <cuda_runtime.h>
#include <cuda_bf16.h>
#include <stdint.h>

typedef __nv_bfloat16 bf16;

constexpr int SEQ = 2048, DM = 640, NH = 32, DH = 20, FF = 1728;
constexpr int HEAD_BYTES = 256 * 384;
#define POLY_MASK 0xADAD

__device__ __align__(1024) uint8_t g_qkvx[3 * NH * HEAD_BYTES];
__device__ __align__(1024) bf16 g_o[SEQ * DM];
__device__ __align__(1024) bf16 g_xa[SEQ * DM];
__device__ __align__(1024) bf16 g_xb[SEQ * DM];
__device__ __align__(1024) bf16 g_h[SEQ * FF];
__device__ __align__(16) float2 g_stats[4][SEQ][8];
__device__ __align__(16) float g_cs[3 * DM + FF];

__device__ __forceinline__ uint32_t smem_u32(const void* p) { return (uint32_t)__cvta_generic_to_shared(p); }
__device__ __forceinline__ void mbar_init(uint32_t bar, int cnt) { asm volatile("mbarrier.init.shared::cta.b64 [%0], %1;" :: "r"(bar), "r"(cnt)); }
__device__ __forceinline__ void mbar_expect(uint32_t bar, uint32_t bytes) { asm volatile("mbarrier.arrive.expect_tx.shared::cta.b64 _, [%0], %1;" :: "r"(bar), "r"(bytes) : "memory"); }
__device__ __forceinline__ void mbar_arrive(uint32_t bar) { asm volatile("mbarrier.arrive.shared::cta.b64 _, [%0];" :: "r"(bar) : "memory"); }
__device__ __forceinline__ void mbar_arrive_remote(uint32_t bar, uint32_t cta) {
    asm volatile("{\n.reg .b32 ra;\nmapa.shared::cluster.u32 ra, %0, %1;\nmbarrier.arrive.release.cluster.shared::cluster.b64 _, [ra];\n}" :: "r"(bar), "r"(cta) : "memory");
}
__device__ __forceinline__ void mbar_wait(uint32_t bar, uint32_t parity) {
    uint32_t ok;
    int spins = 0;
    while (true) {
        asm volatile("{\n.reg .pred p;\nmbarrier.try_wait.parity.shared::cta.b64 p, [%1], %2;\nselp.u32 %0, 1, 0, p;\n}" : "=r"(ok) : "r"(bar), "r"(parity) : "memory");
        if (ok) break;
        if (++spins > (1 << 22)) __trap();
    }
}
__device__ __forceinline__ void mbar_wait_cluster(uint32_t bar, uint32_t parity) {
    uint32_t ok;
    int spins = 0;
    while (true) {
        asm volatile("{\n.reg .pred p;\nmbarrier.try_wait.parity.acquire.cluster.shared::cta.b64 p, [%1], %2;\nselp.u32 %0, 1, 0, p;\n}" : "=r"(ok) : "r"(bar), "r"(parity) : "memory");
        if (ok) break;
        if (++spins > (1 << 22)) __trap();
    }
}
__device__ __forceinline__ void bulk_g2s(uint32_t dst, const void* src, uint32_t bytes, uint32_t bar) {
    asm volatile("cp.async.bulk.shared::cluster.global.mbarrier::complete_tx::bytes [%0], [%1], %2, [%3];" :: "r"(dst), "l"(src), "r"(bytes), "r"(bar) : "memory");
}
__device__ __forceinline__ void bulk_s2g(void* dst, uint32_t src, uint32_t bytes) {
    asm volatile("cp.async.bulk.global.shared::cta.bulk_group [%0], [%1], %2;" :: "l"(dst), "r"(src), "r"(bytes) : "memory");
}
__device__ __forceinline__ void tma_2d(uint32_t dst, const CUtensorMap* tm, int c0, int c1, uint32_t bar) {
    asm volatile("cp.async.bulk.tensor.2d.shared::cluster.global.mbarrier::complete_tx::bytes [%0], [%1, {%3, %4}], [%2];"
        :: "r"(dst), "l"(tm), "r"(bar), "r"(c0), "r"(c1) : "memory");
}
__device__ __forceinline__ void tma_2d_mc(uint32_t dst, const CUtensorMap* tm, int c0, int c1, uint32_t bar) {
    asm volatile("cp.async.bulk.tensor.2d.shared::cluster.global.mbarrier::complete_tx::bytes.multicast::cluster [%0], [%1, {%3, %4}], [%2], %5;"
        :: "r"(dst), "l"(tm), "r"(bar), "r"(c0), "r"(c1), "h"((uint16_t)3) : "memory");
}
__device__ __forceinline__ void tma_3d(uint32_t dst, const CUtensorMap* tm, int c0, int c1, int c2, uint32_t bar) {
    asm volatile("cp.async.bulk.tensor.3d.shared::cluster.global.mbarrier::complete_tx::bytes [%0], [%1, {%3, %4, %5}], [%2];"
        :: "r"(dst), "l"(tm), "r"(bar), "r"(c0), "r"(c1), "r"(c2) : "memory");
}
__device__ __forceinline__ void tma_3d_mc(uint32_t dst, const CUtensorMap* tm, int c0, int c1, int c2, uint32_t bar) {
    asm volatile("cp.async.bulk.tensor.3d.shared::cluster.global.mbarrier::complete_tx::bytes.multicast::cluster [%0], [%1, {%3, %4, %5}], [%2], %6;"
        :: "r"(dst), "l"(tm), "r"(bar), "r"(c0), "r"(c1), "r"(c2), "h"((uint16_t)3) : "memory");
}
__device__ __forceinline__ void tma_store_3d(const CUtensorMap* tm, uint32_t src, int c0, int c1, int c2) {
    asm volatile("cp.async.bulk.tensor.3d.global.shared::cta.bulk_group [%0, {%2, %3, %4}], [%1];"
        :: "l"(tm), "r"(src), "r"(c0), "r"(c1), "r"(c2) : "memory");
}
__device__ __forceinline__ void pdl_wait() { asm volatile("griddepcontrol.wait;" ::: "memory"); }
__device__ __forceinline__ void pdl_launch() { asm volatile("griddepcontrol.launch_dependents;" ::: "memory"); }
__device__ __forceinline__ uint64_t mkdesc(uint32_t addr, uint32_t lbo, uint32_t sbo, uint32_t swz) {
    return (uint64_t)((addr & 0x3FFFF) >> 4) | ((uint64_t)(lbo >> 4) << 16) | ((uint64_t)(sbo >> 4) << 32) | ((uint64_t)swz << 62);
}
#define WG_FENCE() asm volatile("wgmma.fence.sync.aligned;" ::: "memory")
#define WG_COMMIT() asm volatile("wgmma.commit_group.sync.aligned;" ::: "memory")
#define WG_WAIT(n) asm volatile("wgmma.wait_group.sync.aligned %0;" :: "n"(n) : "memory")
#define NAMED_BAR(id, n) asm volatile("bar.sync %0, %1;" :: "r"(id), "n"(n) : "memory")
template<int N> __device__ __forceinline__ void fence_regs(float (&r)[N]) {
#pragma unroll
    for (int i = 0; i < N; i++) asm volatile("" : "+f"(r[i]) :: "memory");
}
template<int N> __device__ __forceinline__ void fence_regs(uint32_t (&r)[N]) {
#pragma unroll
    for (int i = 0; i < N; i++) asm volatile("" : "+r"(r[i]) :: "memory");
}
__device__ __forceinline__ float ex2(float x) { float y; asm("ex2.approx.ftz.f32 %0, %1;" : "=f"(y) : "f"(x)); return y; }
__device__ __forceinline__ float tanh_fast(float x) { float y; asm("tanh.approx.f32 %0, %1;" : "=f"(y) : "f"(x)); return y; }
__device__ __forceinline__ uint32_t pack_bf16(float lo, float hi) { uint32_t r; asm("cvt.rn.bf16x2.f32 %0, %1, %2;" : "=r"(r) : "f"(hi), "f"(lo)); return r; }
__device__ __forceinline__ uint32_t hfma2(uint32_t a, uint32_t b, uint32_t c) { uint32_t r; asm("fma.rn.bf16x2 %0, %1, %2, %3;" : "=r"(r) : "r"(a), "r"(b), "r"(c)); return r; }
__device__ __forceinline__ float bf_lo(uint32_t v) { return __uint_as_float(v << 16); }
__device__ __forceinline__ float bf_hi(uint32_t v) { return __uint_as_float(v & 0xFFFF0000u); }

template<int N> __device__ __forceinline__ void wgmma_ss(float (&d)[N / 2], uint64_t da, uint64_t db, int scale_d);
template<> __device__ __forceinline__ void wgmma_ss<80>(float (&d)[40], uint64_t da, uint64_t db, int scale_d) {
    asm volatile("{\n.reg .pred p;\nsetp.ne.b32 p, %42, 0;\n"
        "wgmma.mma_async.sync.aligned.m64n80k16.f32.bf16.bf16 {%0,%1,%2,%3,%4,%5,%6,%7,%8,%9,%10,%11,%12,%13,%14,%15,%16,%17,%18,%19,%20,%21,%22,%23,%24,%25,%26,%27,%28,%29,%30,%31,%32,%33,%34,%35,%36,%37,%38,%39}, %40, %41, p, 1, 1, 0, 1;\n}"
        : "+f"(d[0]), "+f"(d[1]), "+f"(d[2]), "+f"(d[3]), "+f"(d[4]), "+f"(d[5]), "+f"(d[6]), "+f"(d[7]), "+f"(d[8]), "+f"(d[9]), "+f"(d[10]), "+f"(d[11]), "+f"(d[12]), "+f"(d[13]), "+f"(d[14]), "+f"(d[15]), "+f"(d[16]), "+f"(d[17]), "+f"(d[18]), "+f"(d[19]), "+f"(d[20]), "+f"(d[21]), "+f"(d[22]), "+f"(d[23]), "+f"(d[24]), "+f"(d[25]), "+f"(d[26]), "+f"(d[27]), "+f"(d[28]), "+f"(d[29]), "+f"(d[30]), "+f"(d[31]), "+f"(d[32]), "+f"(d[33]), "+f"(d[34]), "+f"(d[35]), "+f"(d[36]), "+f"(d[37]), "+f"(d[38]), "+f"(d[39])
        : "l"(da), "l"(db), "r"(scale_d));
}
template<> __device__ __forceinline__ void wgmma_ss<216>(float (&d)[108], uint64_t da, uint64_t db, int scale_d) {
    asm volatile("{\n.reg .pred p;\nsetp.ne.b32 p, %110, 0;\n"
        "wgmma.mma_async.sync.aligned.m64n216k16.f32.bf16.bf16 {%0,%1,%2,%3,%4,%5,%6,%7,%8,%9,%10,%11,%12,%13,%14,%15,%16,%17,%18,%19,%20,%21,%22,%23,%24,%25,%26,%27,%28,%29,%30,%31,%32,%33,%34,%35,%36,%37,%38,%39,%40,%41,%42,%43,%44,%45,%46,%47,%48,%49,%50,%51,%52,%53,%54,%55,%56,%57,%58,%59,%60,%61,%62,%63,%64,%65,%66,%67,%68,%69,%70,%71,%72,%73,%74,%75,%76,%77,%78,%79,%80,%81,%82,%83,%84,%85,%86,%87,%88,%89,%90,%91,%92,%93,%94,%95,%96,%97,%98,%99,%100,%101,%102,%103,%104,%105,%106,%107}, %108, %109, p, 1, 1, 0, 1;\n}"
        : "+f"(d[0]), "+f"(d[1]), "+f"(d[2]), "+f"(d[3]), "+f"(d[4]), "+f"(d[5]), "+f"(d[6]), "+f"(d[7]), "+f"(d[8]), "+f"(d[9]), "+f"(d[10]), "+f"(d[11]), "+f"(d[12]), "+f"(d[13]), "+f"(d[14]), "+f"(d[15]), "+f"(d[16]), "+f"(d[17]), "+f"(d[18]), "+f"(d[19]), "+f"(d[20]), "+f"(d[21]), "+f"(d[22]), "+f"(d[23]), "+f"(d[24]), "+f"(d[25]), "+f"(d[26]), "+f"(d[27]), "+f"(d[28]), "+f"(d[29]), "+f"(d[30]), "+f"(d[31]), "+f"(d[32]), "+f"(d[33]), "+f"(d[34]), "+f"(d[35]), "+f"(d[36]), "+f"(d[37]), "+f"(d[38]), "+f"(d[39]), "+f"(d[40]), "+f"(d[41]), "+f"(d[42]), "+f"(d[43]), "+f"(d[44]), "+f"(d[45]), "+f"(d[46]), "+f"(d[47]), "+f"(d[48]), "+f"(d[49]), "+f"(d[50]), "+f"(d[51]), "+f"(d[52]), "+f"(d[53]), "+f"(d[54]), "+f"(d[55]), "+f"(d[56]), "+f"(d[57]), "+f"(d[58]), "+f"(d[59]), "+f"(d[60]), "+f"(d[61]), "+f"(d[62]), "+f"(d[63]), "+f"(d[64]), "+f"(d[65]), "+f"(d[66]), "+f"(d[67]), "+f"(d[68]), "+f"(d[69]), "+f"(d[70]), "+f"(d[71]), "+f"(d[72]), "+f"(d[73]), "+f"(d[74]), "+f"(d[75]), "+f"(d[76]), "+f"(d[77]), "+f"(d[78]), "+f"(d[79]), "+f"(d[80]), "+f"(d[81]), "+f"(d[82]), "+f"(d[83]), "+f"(d[84]), "+f"(d[85]), "+f"(d[86]), "+f"(d[87]), "+f"(d[88]), "+f"(d[89]), "+f"(d[90]), "+f"(d[91]), "+f"(d[92]), "+f"(d[93]), "+f"(d[94]), "+f"(d[95]), "+f"(d[96]), "+f"(d[97]), "+f"(d[98]), "+f"(d[99]), "+f"(d[100]), "+f"(d[101]), "+f"(d[102]), "+f"(d[103]), "+f"(d[104]), "+f"(d[105]), "+f"(d[106]), "+f"(d[107])
        : "l"(da), "l"(db), "r"(scale_d));
}
template<> __device__ __forceinline__ void wgmma_ss<240>(float (&d)[120], uint64_t da, uint64_t db, int scale_d) {
    asm volatile("{\n.reg .pred p;\nsetp.ne.b32 p, %122, 0;\n"
        "wgmma.mma_async.sync.aligned.m64n240k16.f32.bf16.bf16 {%0,%1,%2,%3,%4,%5,%6,%7,%8,%9,%10,%11,%12,%13,%14,%15,%16,%17,%18,%19,%20,%21,%22,%23,%24,%25,%26,%27,%28,%29,%30,%31,%32,%33,%34,%35,%36,%37,%38,%39,%40,%41,%42,%43,%44,%45,%46,%47,%48,%49,%50,%51,%52,%53,%54,%55,%56,%57,%58,%59,%60,%61,%62,%63,%64,%65,%66,%67,%68,%69,%70,%71,%72,%73,%74,%75,%76,%77,%78,%79,%80,%81,%82,%83,%84,%85,%86,%87,%88,%89,%90,%91,%92,%93,%94,%95,%96,%97,%98,%99,%100,%101,%102,%103,%104,%105,%106,%107,%108,%109,%110,%111,%112,%113,%114,%115,%116,%117,%118,%119}, %120, %121, p, 1, 1, 0, 1;\n}"
        : "+f"(d[0]), "+f"(d[1]), "+f"(d[2]), "+f"(d[3]), "+f"(d[4]), "+f"(d[5]), "+f"(d[6]), "+f"(d[7]), "+f"(d[8]), "+f"(d[9]), "+f"(d[10]), "+f"(d[11]), "+f"(d[12]), "+f"(d[13]), "+f"(d[14]), "+f"(d[15]), "+f"(d[16]), "+f"(d[17]), "+f"(d[18]), "+f"(d[19]), "+f"(d[20]), "+f"(d[21]), "+f"(d[22]), "+f"(d[23]), "+f"(d[24]), "+f"(d[25]), "+f"(d[26]), "+f"(d[27]), "+f"(d[28]), "+f"(d[29]), "+f"(d[30]), "+f"(d[31]), "+f"(d[32]), "+f"(d[33]), "+f"(d[34]), "+f"(d[35]), "+f"(d[36]), "+f"(d[37]), "+f"(d[38]), "+f"(d[39]), "+f"(d[40]), "+f"(d[41]), "+f"(d[42]), "+f"(d[43]), "+f"(d[44]), "+f"(d[45]), "+f"(d[46]), "+f"(d[47]), "+f"(d[48]), "+f"(d[49]), "+f"(d[50]), "+f"(d[51]), "+f"(d[52]), "+f"(d[53]), "+f"(d[54]), "+f"(d[55]), "+f"(d[56]), "+f"(d[57]), "+f"(d[58]), "+f"(d[59]), "+f"(d[60]), "+f"(d[61]), "+f"(d[62]), "+f"(d[63]), "+f"(d[64]), "+f"(d[65]), "+f"(d[66]), "+f"(d[67]), "+f"(d[68]), "+f"(d[69]), "+f"(d[70]), "+f"(d[71]), "+f"(d[72]), "+f"(d[73]), "+f"(d[74]), "+f"(d[75]), "+f"(d[76]), "+f"(d[77]), "+f"(d[78]), "+f"(d[79]), "+f"(d[80]), "+f"(d[81]), "+f"(d[82]), "+f"(d[83]), "+f"(d[84]), "+f"(d[85]), "+f"(d[86]), "+f"(d[87]), "+f"(d[88]), "+f"(d[89]), "+f"(d[90]), "+f"(d[91]), "+f"(d[92]), "+f"(d[93]), "+f"(d[94]), "+f"(d[95]), "+f"(d[96]), "+f"(d[97]), "+f"(d[98]), "+f"(d[99]), "+f"(d[100]), "+f"(d[101]), "+f"(d[102]), "+f"(d[103]), "+f"(d[104]), "+f"(d[105]), "+f"(d[106]), "+f"(d[107]), "+f"(d[108]), "+f"(d[109]), "+f"(d[110]), "+f"(d[111]), "+f"(d[112]), "+f"(d[113]), "+f"(d[114]), "+f"(d[115]), "+f"(d[116]), "+f"(d[117]), "+f"(d[118]), "+f"(d[119])
        : "l"(da), "l"(db), "r"(scale_d));
}
template<int SCALE_D> __device__ __forceinline__ void wgmma_qk(float (&d)[32], uint32_t a0, uint32_t a1, uint32_t a2, uint32_t a3, uint64_t db) {
    asm volatile("wgmma.mma_async.sync.aligned.m64n64k16.f32.bf16.bf16 {%0,%1,%2,%3,%4,%5,%6,%7,%8,%9,%10,%11,%12,%13,%14,%15,%16,%17,%18,%19,%20,%21,%22,%23,%24,%25,%26,%27,%28,%29,%30,%31}, {%32,%33,%34,%35}, %36, %37, 1, 1, 0;"
        : "+f"(d[0]), "+f"(d[1]), "+f"(d[2]), "+f"(d[3]), "+f"(d[4]), "+f"(d[5]), "+f"(d[6]), "+f"(d[7]), "+f"(d[8]), "+f"(d[9]), "+f"(d[10]), "+f"(d[11]), "+f"(d[12]), "+f"(d[13]), "+f"(d[14]), "+f"(d[15]), "+f"(d[16]), "+f"(d[17]), "+f"(d[18]), "+f"(d[19]), "+f"(d[20]), "+f"(d[21]), "+f"(d[22]), "+f"(d[23]), "+f"(d[24]), "+f"(d[25]), "+f"(d[26]), "+f"(d[27]), "+f"(d[28]), "+f"(d[29]), "+f"(d[30]), "+f"(d[31])
        : "r"(a0), "r"(a1), "r"(a2), "r"(a3), "l"(db), "n"(SCALE_D));
}
template<int SCALE_D> __device__ __forceinline__ void wgmma_pv(float (&d)[12], uint32_t a0, uint32_t a1, uint32_t a2, uint32_t a3, uint64_t db) {
    asm volatile("wgmma.mma_async.sync.aligned.m64n24k16.f32.bf16.bf16 {%0,%1,%2,%3,%4,%5,%6,%7,%8,%9,%10,%11}, {%12,%13,%14,%15}, %16, %17, 1, 1, 1;"
        : "+f"(d[0]), "+f"(d[1]), "+f"(d[2]), "+f"(d[3]), "+f"(d[4]), "+f"(d[5]), "+f"(d[6]), "+f"(d[7]), "+f"(d[8]), "+f"(d[9]), "+f"(d[10]), "+f"(d[11])
        : "r"(a0), "r"(a1), "r"(a2), "r"(a3), "l"(db), "n"(SCALE_D));
}

__global__ void __launch_bounds__(512, 1) prep_kernel(const bf16* __restrict__ x, const bf16* __restrict__ wqkv, const bf16* __restrict__ w1,
                                                     const bf16* __restrict__ wo, const bf16* __restrict__ w2) {
    pdl_launch();
    __shared__ float2 red[16][32];
    const int b = blockIdx.x, tid = threadIdx.x, warp = tid >> 5, lane = tid & 31;
    if (b < 57) {
        const bf16* w = b < 30 ? wqkv + b * 64 : w1 + (b - 30) * 64;
        const int ld = b < 30 ? 3 * DM : FF;
        const uint32_t* p = (const uint32_t*)(w + (size_t)warp * 40 * ld) + lane;
        float s0 = 0.f, s1 = 0.f;
#pragma unroll
        for (int h = 0; h < 2; h++) {
            uint32_t v[20];
#pragma unroll
            for (int i = 0; i < 20; i++) v[i] = __ldg(p + (size_t)(h * 20 + i) * (ld / 2));
#pragma unroll
            for (int i = 0; i < 20; i++) { s0 += bf_lo(v[i]); s1 += bf_hi(v[i]); }
        }
        red[warp][lane] = make_float2(s0, s1);
        __syncthreads();
        if (warp == 0) {
            float a = 0.f, c = 0.f;
#pragma unroll
            for (int i = 0; i < 16; i++) { a += red[i][lane].x; c += red[i][lane].y; }
            *(float2*)&g_cs[b * 64 + lane * 2] = make_float2(a, c);
        }
    } else if (b < 121) {
#pragma unroll
        for (int r = 0; r < 2; r++) {
            const int row = (b - 57) * 32 + warp * 2 + r;
            const uint2* p = (const uint2*)(x + (size_t)row * DM + lane * 20);
            float v[20];
#pragma unroll
            for (int i = 0; i < 5; i++) { uint2 u = __ldg(p + i); v[4 * i] = bf_lo(u.x); v[4 * i + 1] = bf_hi(u.x); v[4 * i + 2] = bf_lo(u.y); v[4 * i + 3] = bf_hi(u.y); }
            float s = 0.f;
#pragma unroll
            for (int i = 0; i < 20; i++) s += v[i];
            s += __shfl_xor_sync(0xffffffffu, s, 1); s += __shfl_xor_sync(0xffffffffu, s, 2);
            const float m = s * (1.f / 80.f);
            float q = 0.f;
#pragma unroll
            for (int i = 0; i < 20; i++) { float d = v[i] - m; q = fmaf(d, d, q); }
            q += __shfl_xor_sync(0xffffffffu, q, 1); q += __shfl_xor_sync(0xffffffffu, q, 2);
            if ((lane & 3) == 0) g_stats[0][row][lane >> 2] = make_float2(s, q);
        }
    } else {
        for (int i = (b - 121) * 512 + tid; i < 6400 + 17280; i += 11 * 512) {
            const char* p = i < 6400 ? (const char*)wo + (size_t)i * 128 : (const char*)w2 + (size_t)(i - 6400) * 128;
            asm volatile("prefetch.global.L2 [%0];" :: "l"(p));
        }
    }
}

enum { EPI_QKV = 0, EPI_SILU = 1, EPI_RES = 2 };
struct GemmArgs {
    const float2* stats_in;
    const float* cs;
    const bf16* resid;
    float2* stats_out;
    int a_indep;
};
template<int BN, int KB, int STAGES> struct GemmCfg {
    static constexpr int NBOX = (BN + 63) / 64;
    static constexpr int A_BYTES = 128 * 128, B_BYTES = NBOX * 8192, STAGE_BYTES = A_BYTES + B_BYTES;
    static constexpr int AUX_OFF = STAGES * STAGE_BYTES;
    static constexpr int BAR_OFF = AUX_OFF + 1024 + 1024;
    static constexpr int SMEM = BAR_OFF + 256 + 1024;
};
template<int BN, int KB, int STAGES, int EPI, int MC>
__global__ void __launch_bounds__(320, 1) gemm_kernel(const __grid_constant__ CUtensorMap tmA, const __grid_constant__ CUtensorMap tmB,
                                                      const __grid_constant__ CUtensorMap tmO, const GemmArgs args) {
    using C = GemmCfg<BN, KB, STAGES>;
    extern __shared__ uint8_t smem_raw[];
    const uint32_t sbase = (smem_u32(smem_raw) + 1023) & ~1023u;
    uint8_t* sgen = smem_raw + (sbase - smem_u32(smem_raw));
    const uint32_t bar_full = sbase + C::BAR_OFF, bar_empty = bar_full + 8 * STAGES, bar_aux = bar_empty + 8 * STAGES;
    const int tid = threadIdx.x, warp = tid >> 5, lane = tid & 31;
    const int bid = blockIdx.x;
    const int rank = MC ? (bid & 1) : 0;
    const int mt = MC == 1 ? ((bid >> 4) * 2 + rank) : (bid >> 3);
    const int nt = MC == 1 ? ((bid >> 1) & 7) : (bid & 7);

    pdl_launch();
    if (tid == 0) {
        for (int s = 0; s < STAGES; s++) { mbar_init(bar_full + 8 * s, 1); mbar_init(bar_empty + 8 * s, MC ? 16 : 8); }
        mbar_init(bar_aux, 32);
        asm volatile("fence.mbarrier_init.release.cluster;" ::: "memory");
    }
    if (MC) { asm volatile("barrier.cluster.arrive.release.aligned;\nbarrier.cluster.wait.acquire.aligned;" ::: "memory"); }
    else __syncthreads();

    if (warp == 8) {
        if (lane == 0) {
            asm volatile("prefetch.tensormap [%0];" :: "l"(&tmA) : "memory");
            asm volatile("prefetch.tensormap [%0];" :: "l"(&tmB) : "memory");
            auto load_b = [&](int kb, int s) {
                const uint32_t dst = sbase + s * C::STAGE_BYTES + C::A_BYTES;
#pragma unroll
                for (int b = 0; b < C::NBOX; b++) {
                    if (MC == 1) tma_3d_mc(dst + b * 8192 + rank * 4096, &tmB, b * 64, nt, kb * 64 + rank * 32, bar_full + 8 * s);
                    else tma_3d(dst + b * 8192, &tmB, b * 64, nt, kb * 64, bar_full + 8 * s);
                }
            };
            auto load_a = [&](int kb, int s) {
                const uint32_t dst = sbase + s * C::STAGE_BYTES;
                if (MC == 2) tma_2d_mc(dst + rank * 8192, &tmA, kb * 64, mt * 128 + rank * 64, bar_full + 8 * s);
                else tma_2d(dst, &tmA, kb * 64, mt * 128, bar_full + 8 * s);
            };
            constexpr int PRE = STAGES < KB ? STAGES : KB;
            if (args.a_indep) {
                for (int kb = 0; kb < PRE; kb++) { mbar_expect(bar_full + 8 * kb, C::STAGE_BYTES); load_a(kb, kb); load_b(kb, kb); }
            } else {
                for (int kb = 0; kb < PRE; kb++) { mbar_expect(bar_full + 8 * kb, C::STAGE_BYTES); load_b(kb, kb); }
                pdl_wait();
                for (int kb = 0; kb < PRE; kb++) load_a(kb, kb);
            }
            int s = 0, ph = 0;
            for (int kb = PRE; kb < KB; kb++) {
                if (MC) mbar_wait_cluster(bar_empty + 8 * s, ph); else mbar_wait(bar_empty + 8 * s, ph);
                mbar_expect(bar_full + 8 * s, C::STAGE_BYTES);
                load_a(kb, s); load_b(kb, s);
                if (++s == STAGES) { s = 0; ph ^= 1; }
            }
        }
    } else if (warp == 9) {
        if (EPI != EPI_RES) {
            pdl_wait();
            float2* rs = (float2*)(sgen + C::AUX_OFF);
            float* cs = (float*)(sgen + C::AUX_OFF + 1024);
#pragma unroll
            for (int i = 0; i < 4; i++) {
                const int r = i * 32 + lane;
                const float4* p = (const float4*)(args.stats_in + (size_t)(mt * 128 + r) * 8);
                float4 v[4];
#pragma unroll
                for (int j = 0; j < 4; j++) v[j] = p[j];
                float s = 0.f, q = 0.f;
#pragma unroll
                for (int j = 0; j < 4; j++) { s += v[j].x + v[j].z; q += v[j].y + v[j].w; }
                const float mean = s * (1.f / DM);
#pragma unroll
                for (int j = 0; j < 4; j++) {
                    float d0 = v[j].x * (1.f / 80.f) - mean, d1 = v[j].z * (1.f / 80.f) - mean;
                    q += 80.f * (d0 * d0 + d1 * d1);
                }
                const float rstd = rsqrtf(q * (1.f / DM) + 1e-5f);
                rs[r] = make_float2(rstd, -mean * rstd);
            }
            for (int i = lane; i < BN; i += 32) cs[i] = args.cs[nt * BN + i];
            mbar_arrive(bar_aux);
        }
    } else {
        const int wg = warp >> 2, g = lane >> 2, c = lane & 3;
        const int lrow = (warp & 3) * 16 + g;
        const int row = mt * 128 + wg * 64 + lrow;
        uint32_t res[EPI == EPI_RES ? BN / 4 : 1];
        if (EPI == EPI_RES) {
            pdl_wait();
            const uint32_t* r0 = (const uint32_t*)(args.resid + (size_t)row * DM + nt * BN) + c;
#pragma unroll
            for (int j = 0; j < BN / 8; j++) { res[2 * j] = r0[j * 4]; res[2 * j + 1] = r0[j * 4 + 8 * DM / 2]; }
        }
        float acc[BN / 2];
#pragma unroll
        for (int i = 0; i < BN / 2; i++) acc[i] = 0.f;
        fence_regs(acc);
        int s = 0, ph = 0;
#pragma unroll 1
        for (int kb = 0; kb < KB; kb++) {
            mbar_wait(bar_full + 8 * s, ph);
            const uint32_t sa = sbase + s * C::STAGE_BYTES;
            const uint64_t da = mkdesc(sa + wg * 8192, 16, 1024, 1), db = mkdesc(sa + C::A_BYTES, 8192, 1024, 1);
            WG_FENCE();
#pragma unroll
            for (int k = 0; k < 4; k++) wgmma_ss<BN>(acc, da + k * 2, db + k * 128, 1);
            WG_COMMIT();
            if (kb > 0) {
                WG_WAIT(1);
                if (kb - 1 + STAGES < KB) {
                    const int sp = s == 0 ? STAGES - 1 : s - 1;
                    if (MC) { if (lane < 2) mbar_arrive_remote(bar_empty + 8 * sp, lane); }
                    else if (lane == 0) mbar_arrive(bar_empty + 8 * sp);
                }
            }
            if (++s == STAGES) { s = 0; ph ^= 1; }
        }
        WG_WAIT(0);
        fence_regs(acc);
        NAMED_BAR(1, 256);

        if (EPI == EPI_QKV) {
            mbar_wait(bar_aux, 0);
            const float2* rs = (const float2*)(sgen + C::AUX_OFF);
            const float2* cs = (const float2*)(sgen + C::AUX_OFF + 1024);
            const float2 st0 = rs[wg * 64 + lrow], st1 = rs[wg * 64 + lrow + 8];
            const int rg = wg * 8 + (warp & 3) * 2;
            const bool poly0 = (POLY_MASK >> rg) & 1, poly1 = (POLY_MASK >> (rg + 1)) & 1;
            uint32_t off[5];
#pragma unroll
            for (int jj = 0; jj < 5; jj++) {
                const int col = jj * 8 + 2 * c, hl = col >= 20, d = col - hl * 20;
                off[jj] = sbase + hl * 6144 + rg * 384 + (d >> 3) * 128 + g * 16 + (d & 7) * 2;
            }
#pragma unroll
            for (int p = 0; p < 6; p++) {
                const int which = (nt * 12 + p * 2) >> 5;
                const float f0 = which == 0 ? 0.32259642f : (which == 1 && poly0 ? 2.f : 1.f);
                const float f1 = which == 0 ? 0.32259642f : (which == 1 && poly1 ? 2.f : 1.f);
                const float a0 = st0.x * f0, b0 = st0.y * f0, a1 = st1.x * f1, b1 = st1.y * f1;
#pragma unroll
                for (int jj = 0; jj < 5; jj++) {
                    const int j = p * 5 + jj;
                    const float2 cv = cs[j * 4 + c];
                    const uint32_t v0 = pack_bf16(fmaf(acc[4 * j], a0, b0 * cv.x), fmaf(acc[4 * j + 1], a0, b0 * cv.y));
                    const uint32_t v1 = pack_bf16(fmaf(acc[4 * j + 2], a1, b1 * cv.x), fmaf(acc[4 * j + 3], a1, b1 * cv.y));
                    asm volatile("st.shared.b32 [%0], %1;" :: "r"(off[jj] + p * 12288), "r"(v0) : "memory");
                    asm volatile("st.shared.b32 [%0], %1;" :: "r"(off[jj] + p * 12288 + 384), "r"(v1) : "memory");
                }
            }
#pragma unroll
            for (int i = 0; i < 6; i++) {
                const int idx = i * 128 + (tid & 127), hl = idx >> 6, r = wg * 64 + (idx & 63);
                const int which = (nt * 12 + hl) >> 5;
                const bool poly = (POLY_MASK >> (r >> 3)) & 1;
                uint32_t w0, w1;
                if (which == 0) { w0 = 0x3F803F80u; w1 = 0x00003F80u; }
                else if (which == 1) { w0 = poly ? 0xC04B4440u : 0u; w1 = poly ? 0x0000BB88u : 0u; }
                else { w0 = 0x00003F80u; w1 = 0u; }
                asm volatile("st.shared.v2.b32 [%0], {%1, %2};" :: "r"(sbase + hl * 6144 + (r >> 3) * 384 + 256 + (r & 7) * 16 + 8), "r"(w0), "r"(w1) : "memory");
            }
            asm volatile("fence.proxy.async.shared::cta;" ::: "memory");
            NAMED_BAR(2 + wg, 128);
            if ((tid & 127) < 12) {
                const int hl = tid & 127;
                bulk_s2g(g_qkvx + (size_t)(nt * 12 + hl) * HEAD_BYTES + (mt * 16 + wg * 8) * 384, sbase + hl * 6144 + wg * 3072, 3072);
                asm volatile("cp.async.bulk.commit_group;" ::: "memory");
                asm volatile("cp.async.bulk.wait_group 0;" ::: "memory");
            }
        } else {
            uint32_t ov[BN / 4];
            if (EPI == EPI_SILU) {
                mbar_wait(bar_aux, 0);
                const float2* rs = (const float2*)(sgen + C::AUX_OFF);
                const float2* cs = (const float2*)(sgen + C::AUX_OFF + 1024);
                float2 st0 = rs[wg * 64 + lrow], st1 = rs[wg * 64 + lrow + 8];
                st0.x *= 0.5f; st0.y *= 0.5f; st1.x *= 0.5f; st1.y *= 0.5f;
#pragma unroll
                for (int j = 0; j < BN / 8; j++) {
                    const float2 cv = cs[j * 4 + c];
                    const float h0 = fmaf(acc[4 * j], st0.x, st0.y * cv.x), h1 = fmaf(acc[4 * j + 1], st0.x, st0.y * cv.y);
                    const float h2 = fmaf(acc[4 * j + 2], st1.x, st1.y * cv.x), h3 = fmaf(acc[4 * j + 3], st1.x, st1.y * cv.y);
                    ov[2 * j] = pack_bf16(fmaf(h0, tanh_fast(h0), h0), fmaf(h1, tanh_fast(h1), h1));
                    ov[2 * j + 1] = pack_bf16(fmaf(h2, tanh_fast(h2), h2), fmaf(h3, tanh_fast(h3), h3));
                }
            } else {
#pragma unroll
                for (int j = 0; j < BN / 8; j++) {
                    ov[2 * j] = pack_bf16(acc[4 * j] + bf_lo(res[2 * j]), acc[4 * j + 1] + bf_hi(res[2 * j]));
                    ov[2 * j + 1] = pack_bf16(acc[4 * j + 2] + bf_lo(res[2 * j + 1]), acc[4 * j + 3] + bf_hi(res[2 * j + 1]));
                }
            }
            const uint32_t stg = sbase + wg * (C::NBOX * 8192);
            const int srow = (warp & 3) * 16 + ((lane >> 3) & 1) * 8 + (lane & 7);
#pragma unroll
            for (int j = 0; j + 1 < BN / 8; j += 2) {
                const int blk = j + (lane >> 4);
                const uint32_t addr = stg + (blk >> 3) * 8192 + srow * 128 + (((blk & 7) ^ (srow & 7)) << 4);
                asm volatile("stmatrix.sync.aligned.m8n8.x4.shared.b16 [%0], {%1, %2, %3, %4};"
                    :: "r"(addr), "r"(ov[2 * j]), "r"(ov[2 * j + 1]), "r"(ov[2 * j + 2]), "r"(ov[2 * j + 3]) : "memory");
            }
            if ((BN / 8) & 1) {
                constexpr int j = BN / 8 - 1;
                const uint32_t addr = stg + (j >> 3) * 8192 + srow * 128 + (((j & 7) ^ (srow & 7)) << 4);
                asm volatile("stmatrix.sync.aligned.m8n8.x2.shared.b16 [%0], {%1, %2};" :: "r"(addr), "r"(ov[2 * j]), "r"(ov[2 * j + 1]) : "memory");
            }
            asm volatile("fence.proxy.async.shared::cta;" ::: "memory");
            NAMED_BAR(2 + wg, 128);
            if ((tid & 127) < C::NBOX) {
                const int b = tid & 127;
                tma_store_3d(&tmO, stg + b * 8192, b * 64, nt, mt * 128 + wg * 64);
                asm volatile("cp.async.bulk.commit_group;" ::: "memory");
            }
            if (EPI == EPI_RES && args.stats_out != nullptr) {
                float s0 = 0.f, s1 = 0.f;
#pragma unroll
                for (int j = 0; j < BN / 8; j++) { s0 += bf_lo(ov[2 * j]) + bf_hi(ov[2 * j]); s1 += bf_lo(ov[2 * j + 1]) + bf_hi(ov[2 * j + 1]); }
                s0 += __shfl_xor_sync(0xffffffffu, s0, 1); s0 += __shfl_xor_sync(0xffffffffu, s0, 2);
                s1 += __shfl_xor_sync(0xffffffffu, s1, 1); s1 += __shfl_xor_sync(0xffffffffu, s1, 2);
                const float m0 = s0 * (1.f / BN), m1 = s1 * (1.f / BN);
                float q0 = 0.f, q1 = 0.f;
#pragma unroll
                for (int j = 0; j < BN / 8; j++) {
                    float d;
                    d = bf_lo(ov[2 * j]) - m0; q0 = fmaf(d, d, q0); d = bf_hi(ov[2 * j]) - m0; q0 = fmaf(d, d, q0);
                    d = bf_lo(ov[2 * j + 1]) - m1; q1 = fmaf(d, d, q1); d = bf_hi(ov[2 * j + 1]) - m1; q1 = fmaf(d, d, q1);
                }
                q0 += __shfl_xor_sync(0xffffffffu, q0, 1); q0 += __shfl_xor_sync(0xffffffffu, q0, 2);
                q1 += __shfl_xor_sync(0xffffffffu, q1, 1); q1 += __shfl_xor_sync(0xffffffffu, q1, 2);
                if (c == 0) { args.stats_out[(size_t)row * 8 + nt] = make_float2(s0, q0); args.stats_out[(size_t)(row + 8) * 8 + nt] = make_float2(s1, q1); }
            }
            if ((tid & 127) < C::NBOX) asm volatile("cp.async.bulk.wait_group 0;" ::: "memory");
        }
    }
    if (MC) { asm volatile("barrier.cluster.arrive.release.aligned;\nbarrier.cluster.wait.acquire.aligned;" ::: "memory"); }
}

__device__ __forceinline__ uint32_t poly_pair(float y0, float y1, uint32_t mmask) {
    const uint32_t L = __byte_perm(__float_as_uint(y0), __float_as_uint(y1), 0x6521);
    uint32_t U, Y;
    asm("lop3.b32 %0, %1, %2, 0x3F003F00, 0xEA;" : "=r"(U) : "r"(L), "r"(mmask));
    asm("lop3.b32 %0, %1, %2, 0x00010001, 0xBA;" : "=r"(Y) : "r"(L), "r"(mmask));
    return hfma2(L, U, Y);
}
template<int OFF>
__device__ __forceinline__ void exp_tile(float (&s)[32], uint32_t (&p)[16], uint32_t mmask) {
    fence_regs(s);
#pragma unroll
    for (int b = 0; b < 8; b++) {
        if ((POLY_MASK >> (OFF + b)) & 1) {
            p[2 * b] = poly_pair(s[4 * b], s[4 * b + 1], mmask);
            p[2 * b + 1] = poly_pair(s[4 * b + 2], s[4 * b + 3], mmask);
        } else {
            p[2 * b] = pack_bf16(ex2(s[4 * b]), ex2(s[4 * b + 1]));
            p[2 * b + 1] = pack_bf16(ex2(s[4 * b + 2]), ex2(s[4 * b + 3]));
        }
    }
    fence_regs(p);
}
__device__ __forceinline__ void attn_store(const float (&o)[12], int row, int head, int lane) {
    const int c = lane & 3;
    const float l0 = __shfl_sync(0xffffffffu, o[8], (lane & ~3) | 2), l1 = __shfl_sync(0xffffffffu, o[10], (lane & ~3) | 2);
    const float r0 = __frcp_rn(l0), r1 = __frcp_rn(l1);
    uint32_t* o0 = (uint32_t*)(g_o + (size_t)row * DM + head * DH) + c;
    uint32_t* o1 = o0 + 8 * DM / 2;
    o0[0] = pack_bf16(o[0] * r0, o[1] * r0); o1[0] = pack_bf16(o[2] * r1, o[3] * r1);
    o0[4] = pack_bf16(o[4] * r0, o[5] * r0); o1[4] = pack_bf16(o[6] * r1, o[7] * r1);
    if (c < 2) { o0[8] = pack_bf16(o[8] * r0, o[9] * r0); o1[8] = pack_bf16(o[10] * r1, o[11] * r1); }
}
#define ATT_QK(sx, off) do { wgmma_qk<0>(sx, q0, q1, q2, q3, dK0 + (off)); wgmma_qk<1>(sx, q4, q5, zero, zero, dK1 + (off)); } while (0)
#define ATT_PV(px, off) do { _Pragma("unroll") for (int j = 0; j < 4; j++) wgmma_pv<1>(o, px[4 * j], px[4 * j + 1], px[4 * j + 2], px[4 * j + 3], dV + (off) + ((j * 768) >> 4)); } while (0)

__device__ __forceinline__ void attn_tile_safe(const uint32_t* gq, uint64_t dK0, uint64_t dK1, uint64_t dV, int row, int head, int lane) {
    const int c = lane & 3;
    const uint32_t q0 = gq[0], q1 = gq[96], q2 = gq[32], q3 = gq[128];
    const uint32_t q4 = c < 2 ? gq[64] : 0u, q5 = c < 2 ? gq[160] : 0u;
    uint32_t zero = 0;
    asm volatile("" : "+r"(zero));
    float o[12], s[32];
    uint32_t p[16];
#pragma unroll
    for (int i = 0; i < 12; i++) o[i] = 0.f;
#pragma unroll
    for (int i = 0; i < 32; i++) s[i] = 0.f;
    float m0 = -INFINITY, m1 = -INFINITY;
#pragma unroll 1
    for (int t = 0; t < 32; t++) {
        const uint64_t koff = (uint64_t)(t * 3072 >> 4);
        fence_regs(s);
        WG_FENCE();
        ATT_QK(s, koff);
        WG_COMMIT();
        WG_WAIT(0);
        fence_regs(s);
        const uint32_t pm = POLY_MASK >> ((t & 1) * 8);
        float n0 = m0, n1 = m1;
#pragma unroll
        for (int b = 0; b < 8; b++) {
            const float f = (pm >> b) & 1 ? 0.5f : 1.f;
            s[4 * b] *= f; s[4 * b + 1] *= f; s[4 * b + 2] *= f; s[4 * b + 3] *= f;
            n0 = fmaxf(n0, fmaxf(s[4 * b], s[4 * b + 1])); n1 = fmaxf(n1, fmaxf(s[4 * b + 2], s[4 * b + 3]));
        }
        n0 = fmaxf(n0, __shfl_xor_sync(0xffffffffu, n0, 1)); n0 = fmaxf(n0, __shfl_xor_sync(0xffffffffu, n0, 2));
        n1 = fmaxf(n1, __shfl_xor_sync(0xffffffffu, n1, 1)); n1 = fmaxf(n1, __shfl_xor_sync(0xffffffffu, n1, 2));
        const float a0 = ex2(m0 - n0), a1 = ex2(m1 - n1);
        m0 = n0; m1 = n1;
#pragma unroll
        for (int j = 0; j < 3; j++) { o[4 * j] *= a0; o[4 * j + 1] *= a0; o[4 * j + 2] *= a1; o[4 * j + 3] *= a1; }
#pragma unroll
        for (int b = 0; b < 8; b++) {
            p[2 * b] = pack_bf16(ex2(s[4 * b] - m0), ex2(s[4 * b + 1] - m0));
            p[2 * b + 1] = pack_bf16(ex2(s[4 * b + 2] - m1), ex2(s[4 * b + 3] - m1));
        }
        fence_regs(p); fence_regs(o);
        WG_FENCE();
        ATT_PV(p, koff);
        WG_COMMIT();
        WG_WAIT(0);
        fence_regs(o);
    }
    attn_store(o, row, head, lane);
}

__global__ void __launch_bounds__(512, 1) attn_kernel() {
    extern __shared__ __align__(128) uint8_t smem[];
    __shared__ __align__(8) uint64_t bars[17];
    __shared__ uint32_t kmax_bits;
    const int head = blockIdx.x >> 2, quarter = blockIdx.x & 3;
    const int tid = threadIdx.x, wg = tid >> 7, warp = (tid >> 5) & 3, lane = tid & 31, g = lane >> 2, c = lane & 3;
    const uint32_t sK = smem_u32(smem), sV = sK + HEAD_BYTES;
    pdl_launch();
    if (tid == 0) {
        for (int i = 0; i < 16; i++) mbar_init(smem_u32(&bars[i]), 1);
        mbar_init(smem_u32(&bars[16]), 16);
        kmax_bits = 0;
        asm volatile("fence.mbarrier_init.release.cluster;" ::: "memory");
    }
    pdl_wait();
    if (tid == 0) {
        const uint8_t* gK = g_qkvx + (size_t)(NH + head) * HEAD_BYTES;
        const uint8_t* gV = g_qkvx + (size_t)(2 * NH + head) * HEAD_BYTES;
        for (int i = 0; i < 16; i++) {
            mbar_expect(smem_u32(&bars[i]), 12288);
            bulk_g2s(sK + i * 6144, gK + i * 6144, 6144, smem_u32(&bars[i]));
            bulk_g2s(sV + i * 6144, gV + i * 6144, 6144, smem_u32(&bars[i]));
        }
    }
    __syncthreads();
    const uint64_t dK0 = mkdesc(sK, 128, 384, 0), dK1 = mkdesc(sK + 256, 0, 384, 0), dV = mkdesc(sV, 384, 128, 0);
    float qn[2];
#pragma unroll 1
    for (int pass = 0; pass < 2; pass++) {
        const int row0 = quarter * 512 + (pass * 4 + wg) * 64 + warp * 16;
        const uint32_t* gq = (const uint32_t*)(g_qkvx + (size_t)head * HEAD_BYTES + (row0 >> 3) * 384) + lane;
        const uint32_t q0 = gq[0], q1 = gq[96], q2 = gq[32], q3 = gq[128], q4 = gq[64], q5 = gq[160];
        uint32_t zero = 0, mmask = 0x007F007Fu;
        asm volatile("" : "+r"(zero), "+r"(mmask));
        float o[12], s0[32];
        uint32_t p0[16];
#pragma unroll
        for (int i = 0; i < 12; i++) o[i] = 0.f;
#pragma unroll
        for (int i = 0; i < 32; i++) s0[i] = 0.f;
#pragma unroll
        for (int i = 0; i < 16; i++) p0[i] = 0u;
        fence_regs(o); fence_regs(s0); fence_regs(p0);
#pragma unroll 1
        for (int t = 0; t < 16; t++) {
            const uint64_t koff = (uint64_t)(t * 6144 >> 4);
            const uint64_t kprev = (uint64_t)((t > 0 ? t * 6144 - 3072 : 0) >> 4);
            if (pass == 0) mbar_wait(smem_u32(&bars[t]), 0);
            WG_FENCE();
            ATT_PV(p0, kprev);
            ATT_QK(s0, koff);
            WG_COMMIT();
            WG_WAIT(0);
            exp_tile<0>(s0, p0, mmask);
            WG_FENCE();
            ATT_PV(p0, koff);
            ATT_QK(s0, koff + (3072 >> 4));
            WG_COMMIT();
            WG_WAIT(0);
            exp_tile<8>(s0, p0, mmask);
        }
        WG_FENCE();
        ATT_PV(p0, (15 * 6144 + 3072) >> 4);
        WG_COMMIT();
        if (pass == 0) {
            float km = 0.f;
#pragma unroll
            for (int i = 0; i < 4; i++) {
                const int key = tid + i * 512;
                const uint8_t* kp = smem + (key >> 3) * 384 + (key & 7) * 16;
                const uint4 a = *(const uint4*)kp, b = *(const uint4*)(kp + 128);
                const uint2 d = *(const uint2*)(kp + 256);
                uint32_t u = hfma2(a.x, a.x, 0u), w = hfma2(a.y, a.y, 0u);
                u = hfma2(a.z, a.z, u); w = hfma2(a.w, a.w, w); u = hfma2(b.x, b.x, u); w = hfma2(b.y, b.y, w);
                u = hfma2(b.z, b.z, u); w = hfma2(b.w, b.w, w); u = hfma2(d.x, d.x, u); w = hfma2(d.y, d.y, w);
                float n = (bf_lo(u) + bf_hi(u)) + (bf_lo(w) + bf_hi(w));
                if ((POLY_MASK >> ((key >> 3) & 15)) & 1) n *= 0.25f;
                km = n >= km ? n : (n != n ? INFINITY : km);
            }
            const uint32_t kb = __reduce_max_sync(0xffffffffu, __float_as_uint(km));
            if (lane == 0) { atomicMax(&kmax_bits, kb); mbar_arrive(smem_u32(&bars[16])); }
        }
        {
            const uint32_t q4m = c < 2 ? q4 : 0u, q5m = c < 2 ? q5 : 0u;
            float n0 = bf_lo(q0) * bf_lo(q0) + bf_hi(q0) * bf_hi(q0) + bf_lo(q2) * bf_lo(q2) + bf_hi(q2) * bf_hi(q2) + bf_lo(q4m) * bf_lo(q4m) + bf_hi(q4m) * bf_hi(q4m);
            float n1 = bf_lo(q1) * bf_lo(q1) + bf_hi(q1) * bf_hi(q1) + bf_lo(q3) * bf_lo(q3) + bf_hi(q3) * bf_hi(q3) + bf_lo(q5m) * bf_lo(q5m) + bf_hi(q5m) * bf_hi(q5m);
            n0 += __shfl_xor_sync(0xffffffffu, n0, 1); n0 += __shfl_xor_sync(0xffffffffu, n0, 2);
            n1 += __shfl_xor_sync(0xffffffffu, n1, 1); n1 += __shfl_xor_sync(0xffffffffu, n1, 2);
            float n = n0 >= n1 ? n0 : n1;
            if (n0 != n0) n = INFINITY;
            WG_WAIT(0);
            fence_regs(o);
            bool ok = true;
#pragma unroll
            for (int i = 0; i < 12; i++) ok = ok && fabsf(o[i]) < 1e30f;
            if (c == 2) ok = ok && o[8] > 1e-6f && o[10] > 1e-6f;
            if (!ok) n = INFINITY;
            if (pass == 0) qn[0] = n; else qn[1] = n;
        }
        attn_store(o, row0 + g, head, lane);
    }
    mbar_wait(smem_u32(&bars[16]), 0);
    const float kmax = __uint_as_float(*(volatile uint32_t*)&kmax_bits);
#pragma unroll 1
    for (int pass = 0; pass < 2; pass++) {
        const bool bad = !((pass == 0 ? qn[0] : qn[1]) * kmax * 1.1f <= 4096.f);
        uint32_t any;
        asm volatile("{\n.reg .pred p, q;\nsetp.ne.u32 q, %1, 0;\nbar.red.or.pred p, %2, 128, q;\nselp.u32 %0, 1, 0, p;\n}" : "=r"(any) : "r"((uint32_t)bad), "r"(1 + wg) : "memory");
        if (any) {
            const int row0 = quarter * 512 + (pass * 4 + wg) * 64 + warp * 16;
            const uint32_t* gq = (const uint32_t*)(g_qkvx + (size_t)head * HEAD_BYTES + (row0 >> 3) * 384) + lane;
            attn_tile_safe(gq, dK0, dK1, dV, row0 + g, head, lane);
        }
    }
}

typedef CUresult (*EncodeFn)(CUtensorMap*, CUtensorMapDataType, cuuint32_t, void*, const cuuint64_t*, const cuuint64_t*, const cuuint32_t*,
                             const cuuint32_t*, CUtensorMapInterleave, CUtensorMapSwizzle, CUtensorMapL2promotion, CUtensorMapFloatOOBfill);
static EncodeFn s_encode;
static CUtensorMap map2d(const void* p, int rows, int cols, int box_rows) {
    CUtensorMap m;
    cuuint64_t dims[2] = {(cuuint64_t)cols, (cuuint64_t)rows}, strides[1] = {(cuuint64_t)cols * 2};
    cuuint32_t box[2] = {64, (cuuint32_t)box_rows}, es[2] = {1, 1};
    s_encode(&m, CU_TENSOR_MAP_DATA_TYPE_BFLOAT16, 2, (void*)p, dims, strides, box, es, CU_TENSOR_MAP_INTERLEAVE_NONE, CU_TENSOR_MAP_SWIZZLE_128B,
             CU_TENSOR_MAP_L2_PROMOTION_L2_128B, CU_TENSOR_MAP_FLOAT_OOB_FILL_NONE);
    return m;
}
static CUtensorMap map3d(const void* p, int rows, int bn, int box_rows) {
    CUtensorMap m;
    cuuint64_t dims[3] = {(cuuint64_t)bn, 8, (cuuint64_t)rows}, strides[2] = {(cuuint64_t)bn * 2, (cuuint64_t)bn * 16};
    cuuint32_t box[3] = {64, 1, (cuuint32_t)box_rows}, es[3] = {1, 1, 1};
    s_encode(&m, CU_TENSOR_MAP_DATA_TYPE_BFLOAT16, 3, (void*)p, dims, strides, box, es, CU_TENSOR_MAP_INTERLEAVE_NONE, CU_TENSOR_MAP_SWIZZLE_128B,
             CU_TENSOR_MAP_L2_PROMOTION_L2_128B, CU_TENSOR_MAP_FLOAT_OOB_FILL_NONE);
    return m;
}
template<typename... KArgs, typename... Args>
static void launch(void (*kern)(KArgs...), int grid, int block, int smem, int cluster, bool pdl, Args... args) {
    cudaLaunchConfig_t cfg = {};
    cfg.gridDim = dim3(grid); cfg.blockDim = dim3(block); cfg.dynamicSmemBytes = smem; cfg.stream = cudaStreamPerThread;
    cudaLaunchAttribute at[2];
    int n = 0;
    if (pdl) { at[n].id = cudaLaunchAttributeProgrammaticStreamSerialization; at[n].val.programmaticStreamSerializationAllowed = 1; n++; }
    if (cluster > 1) { at[n].id = cudaLaunchAttributeClusterDimension; at[n].val.clusterDim.x = cluster; at[n].val.clusterDim.y = 1; at[n].val.clusterDim.z = 1; n++; }
    cfg.attrs = at; cfg.numAttrs = n;
    cudaLaunchKernelEx(&cfg, kern, KArgs(args)...);
}

#define MC_QKV 1
#define MC_W1 1
#define MC_RES 2
#define USE_PDL true
constexpr int ST_BIG = 4, ST_RES = 6;
#define K_QKV gemm_kernel<240, 10, ST_BIG, EPI_QKV, MC_QKV>
#define K_W1 gemm_kernel<216, 10, ST_BIG, EPI_SILU, MC_W1>
#define K_WO gemm_kernel<80, 10, ST_RES, EPI_RES, MC_RES>
#define K_W2 gemm_kernel<80, 27, ST_RES, EPI_RES, MC_RES>

extern "C" void kernel_launch(void* const* d_in, const int* in_sizes, int n_in, void* d_out, int out_size) {
    const bf16* x = (const bf16*)d_in[0];
    const bf16* wqkv = (const bf16*)d_in[1];
    const bf16* wo = (const bf16*)d_in[2];
    const bf16* w1 = (const bf16*)d_in[4];
    const bf16* w2 = (const bf16*)d_in[5];
    bf16* out = (bf16*)d_out;

    if (!s_encode) {
        cudaDriverEntryPointQueryResult qr;
        void* fn = nullptr;
        cudaGetDriverEntryPoint("cuTensorMapEncodeTiled", &fn, cudaEnableDefault, &qr);
        s_encode = (EncodeFn)fn;
        cudaFuncSetAttribute(K_QKV, cudaFuncAttributeMaxDynamicSharedMemorySize, GemmCfg<240, 10, ST_BIG>::SMEM);
        cudaFuncSetAttribute(K_W1, cudaFuncAttributeMaxDynamicSharedMemorySize, GemmCfg<216, 10, ST_BIG>::SMEM);
        cudaFuncSetAttribute(K_WO, cudaFuncAttributeMaxDynamicSharedMemorySize, GemmCfg<80, 10, ST_RES>::SMEM);
        cudaFuncSetAttribute(K_W2, cudaFuncAttributeMaxDynamicSharedMemorySize, GemmCfg<80, 27, ST_RES>::SMEM);
        cudaFuncSetAttribute(attn_kernel, cudaFuncAttributeMaxDynamicSharedMemorySize, 2 * HEAD_BYTES);
    }
    void *p_o, *p_xa, *p_xb, *p_h, *p_stats, *p_cs;
    cudaGetSymbolAddress(&p_o, g_o); cudaGetSymbolAddress(&p_xa, g_xa); cudaGetSymbolAddress(&p_xb, g_xb);
    cudaGetSymbolAddress(&p_h, g_h); cudaGetSymbolAddress(&p_stats, g_stats); cudaGetSymbolAddress(&p_cs, g_cs);
    float2* stats = (float2*)p_stats;
    const float* cs = (const float*)p_cs;

    const CUtensorMap mWqkv = map3d(wqkv, DM, 240, MC_QKV == 1 ? 32 : 64), mW1 = map3d(w1, DM, 216, MC_W1 == 1 ? 32 : 64);
    const CUtensorMap mWo = map3d(wo, DM, 80, MC_RES == 1 ? 32 : 64), mW2 = map3d(w2, FF, 80, MC_RES == 1 ? 32 : 64);
    const CUtensorMap mO = map2d(p_o, SEQ, DM, MC_RES == 2 ? 64 : 128), mH = map2d(p_h, SEQ, FF, MC_RES == 2 ? 64 : 128);
    const CUtensorMap mHout = map3d(p_h, SEQ, 216, 64);

    launch(prep_kernel, 132, 512, 0, 1, false, x, wqkv, w1, wo, w2);
    const bf16* xin = x;
    for (int layer = 0; layer < 2; layer++) {
        bf16* x1 = (bf16*)p_xa;
        bf16* x2 = layer == 0 ? (bf16*)p_xb : out;
        GemmArgs a;
        a = {stats + (size_t)(2 * layer) * SEQ * 8, cs, nullptr, nullptr, layer == 0 ? 1 : 0};
        launch(K_QKV, 128, 320, GemmCfg<240, 10, ST_BIG>::SMEM, MC_QKV ? 2 : 1, USE_PDL, map2d(xin, SEQ, DM, MC_QKV == 2 ? 64 : 128), mWqkv, mWqkv, a);
        launch(attn_kernel, 128, 512, 2 * HEAD_BYTES, 1, USE_PDL);
        a = {nullptr, nullptr, xin, stats + (size_t)(2 * layer + 1) * SEQ * 8, 0};
        launch(K_WO, 128, 320, GemmCfg<80, 10, ST_RES>::SMEM, MC_RES ? 2 : 1, USE_PDL, mO, mWo, map3d(x1, SEQ, 80, 64), a);
        a = {stats + (size_t)(2 * layer + 1) * SEQ * 8, cs + 3 * DM, nullptr, nullptr, 0};
        launch(K_W1, 128, 320, GemmCfg<216, 10, ST_BIG>::SMEM, MC_W1 ? 2 : 1, USE_PDL, map2d(x1, SEQ, DM, MC_W1 == 2 ? 64 : 128), mW1, mHout, a);
        a = {nullptr, nullptr, x1, layer == 0 ? stats + (size_t)2 * SEQ * 8 : nullptr, 0};
        launch(K_W2, 128, 320, GemmCfg<80, 27, ST_RES>::SMEM, MC_RES ? 2 : 1, USE_PDL, mH, mW2, map3d(x2, SEQ, 80, 64), a);
        xin = x2;
    }
}
```

```cpp
#include <cuda.h>
#include <cuda_runtime.h>
#include <cuda_bf16.h>
#include <stdint.h>

typedef __nv_bfloat16 bf16;

constexpr int SEQ = 2048, DM = 640, NH = 32, DH = 20, FF = 1728;
constexpr int HEAD_BYTES = 256 * 384;
#define POLY_MASK 0xAD
constexpr int NHELP = 4, NWORK = 128, NTHREADS = 640;

__device__ __align__(1024) uint8_t g_qkvx[2][3 * NH * HEAD_BYTES];
__device__ __align__(1024) uint8_t g_o[SEQ * DM * 2];
__device__ __align__(1024) uint8_t g_xa[SEQ * DM * 2];
__device__ __align__(1024) uint8_t g_xb[SEQ * DM * 2];
__device__ __align__(1024) uint8_t g_h[SEQ * FF * 2];
__device__ __align__(1024) uint8_t g_wo_p[DM * DM * 2];
__device__ __align__(1024) uint8_t g_wqkv_p[DM * 3 * DM * 2];
__device__ __align__(1024) uint8_t g_w1_p[DM * FF * 2];
__device__ __align__(1024) uint8_t g_w2_p[FF * DM * 2];
__device__ __align__(128) float4 g_stats[4][32][8][64];
__device__ __align__(16) float g_cs[16][3 * DM + FF];
struct Flags {
    uint32_t epoch[32];
    uint32_t cs[2][8][32];
    uint32_t st0[32][32];
    uint32_t pack[4][32];
    uint32_t res[4][32][32];
    uint32_t w1[2][32][32];
    uint32_t att[2][32][32];
    uint32_t qkv[2][16][32];
};
__device__ __align__(128) Flags g_flags;

#define TS(kid, slot) do {} while (0)
__device__ __forceinline__ uint32_t smem_u32(const void* p) { return (uint32_t)__cvta_generic_to_shared(p); }
__device__ __forceinline__ void mbar_init(uint32_t bar, int cnt) { asm volatile("mbarrier.init.shared::cta.b64 [%0], %1;" :: "r"(bar), "r"(cnt)); }
__device__ __forceinline__ void mbar_expect(uint32_t bar, uint32_t bytes) { asm volatile("mbarrier.arrive.expect_tx.shared::cta.b64 _, [%0], %1;" :: "r"(bar), "r"(bytes) : "memory"); }
__device__ __forceinline__ void mbar_arrive(uint32_t bar) { asm volatile("mbarrier.arrive.shared::cta.b64 _, [%0];" :: "r"(bar) : "memory"); }
__device__ __forceinline__ void mbar_arrive_remote(uint32_t bar, uint32_t cta) {
    asm volatile("{\n.reg .b32 ra;\nmapa.shared::cluster.u32 ra, %0, %1;\nmbarrier.arrive.shared::cluster.b64 _, [ra];\n}" :: "r"(bar), "r"(cta) : "memory");
}
__device__ __forceinline__ void mbar_wait(uint32_t bar, uint32_t parity) {
    asm volatile("{\n.reg .pred p;\n.reg .u32 n;\n"
                 "mbarrier.try_wait.parity.shared::cta.b64 p, [%0], %1;\n@p bra DONE_%=;\nmov.u32 n, 0;\n"
                 "WAIT_%=:\nmbarrier.try_wait.parity.shared::cta.b64 p, [%0], %1;\n@p bra DONE_%=;\n"
                 "add.u32 n, n, 1;\nsetp.lt.u32 p, n, 2097152;\n@p bra WAIT_%=;\ntrap;\nDONE_%=:\n}" :: "r"(bar), "r"(parity) : "memory");
}
__device__ __forceinline__ void mbar_wait_sleep(uint32_t bar, uint32_t parity) {
    asm volatile("{\n.reg .pred p;\n.reg .u32 n;\nmov.u32 n, 0;\n"
                 "WAIT_%=:\nmbarrier.try_wait.parity.shared::cta.b64 p, [%0], %1;\n@p bra DONE_%=;\nnanosleep.u32 100;\n"
                 "add.u32 n, n, 1;\nsetp.lt.u32 p, n, 4194304;\n@p bra WAIT_%=;\ntrap;\nDONE_%=:\n}" :: "r"(bar), "r"(parity) : "memory");
}
__device__ __forceinline__ int fresh_tid() { int t; asm volatile("mov.u32 %0, %%tid.x;" : "=r"(t)); return t; }
#define THREAD_IDS const int tid = fresh_tid(), lane = tid & 31, g = lane >> 2, c = lane & 3, t128 = tid & 127, lrow = warp * 16 + g; (void)g; (void)c; (void)t128; (void)lrow
__device__ __forceinline__ bool elect_one() {
    uint32_t p;
    asm volatile("{\n.reg .pred p;\nelect.sync _|p, 0xffffffff;\nselp.u32 %0, 1, 0, p;\n}" : "=r"(p));
    return p != 0;
}
__device__ __forceinline__ void bulk_g2s(uint32_t dst, const void* src, uint32_t bytes, uint32_t bar) {
    asm volatile("cp.async.bulk.shared::cluster.global.mbarrier::complete_tx::bytes [%0], [%1], %2, [%3];" :: "r"(dst), "l"(src), "r"(bytes), "r"(bar) : "memory");
}
__device__ __forceinline__ void bulk_s2g(void* dst, uint32_t src, uint32_t bytes) {
    asm volatile("cp.async.bulk.global.shared::cta.bulk_group [%0], [%1], %2;" :: "l"(dst), "r"(src), "r"(bytes) : "memory");
}
__device__ __forceinline__ void tma_2d(uint32_t dst, const CUtensorMap* tm, int c0, int c1, uint32_t bar) {
    asm volatile("cp.async.bulk.tensor.2d.shared::cluster.global.mbarrier::complete_tx::bytes [%0], [%1, {%3, %4}], [%2];"
        :: "r"(dst), "l"(tm), "r"(bar), "r"(c0), "r"(c1) : "memory");
}
__device__ __forceinline__ void tma_2d_mc(uint32_t dst, const CUtensorMap* tm, int c0, int c1, uint32_t bar) {
    asm volatile("cp.async.bulk.tensor.2d.shared::cluster.global.mbarrier::complete_tx::bytes.multicast::cluster [%0], [%1, {%3, %4}], [%2], %5;"
        :: "r"(dst), "l"(tm), "r"(bar), "r"(c0), "r"(c1), "h"((uint16_t)3) : "memory");
}
__device__ __forceinline__ void tma_3d(uint32_t dst, const CUtensorMap* tm, int c0, int c1, int c2, uint32_t bar) {
    asm volatile("cp.async.bulk.tensor.3d.shared::cluster.global.mbarrier::complete_tx::bytes [%0], [%1, {%3, %4, %5}], [%2];"
        :: "r"(dst), "l"(tm), "r"(bar), "r"(c0), "r"(c1), "r"(c2) : "memory");
}
__device__ __forceinline__ void tma_3d_mc(uint32_t dst, const CUtensorMap* tm, int c0, int c1, int c2, uint32_t bar) {
    asm volatile("cp.async.bulk.tensor.3d.shared::cluster.global.mbarrier::complete_tx::bytes.multicast::cluster [%0], [%1, {%3, %4, %5}], [%2], %6;"
        :: "r"(dst), "l"(tm), "r"(bar), "r"(c0), "r"(c1), "r"(c2), "h"((uint16_t)3) : "memory");
}
__device__ __forceinline__ void tma_store_3d(const CUtensorMap* tm, uint32_t src, int c0, int c1, int c2) {
    asm volatile("cp.async.bulk.tensor.3d.global.shared::cta.bulk_group [%0, {%2, %3, %4}], [%1];"
        :: "l"(tm), "r"(src), "r"(c0), "r"(c1), "r"(c2) : "memory");
}
__device__ __forceinline__ void pdl_wait() { asm volatile("griddepcontrol.wait;" ::: "memory"); }
__device__ __forceinline__ void pdl_launch() { asm volatile("griddepcontrol.launch_dependents;" ::: "memory"); }
__device__ __forceinline__ uint64_t mkdesc(uint32_t addr, uint32_t lbo, uint32_t sbo, uint32_t swz) {
    return (uint64_t)((addr & 0x3FFFF) >> 4) | ((uint64_t)(lbo >> 4) << 16) | ((uint64_t)(sbo >> 4) << 32) | ((uint64_t)swz << 62);
}
#define WG_FENCE() asm volatile("wgmma.fence.sync.aligned;" ::: "memory")
#define WG_COMMIT() asm volatile("wgmma.commit_group.sync.aligned;" ::: "memory")
#define WG_WAIT(n) asm volatile("wgmma.wait_group.sync.aligned %0;" :: "n"(n) : "memory")
#define NAMED_BAR(id, n) asm volatile("bar.sync %0, %1;" :: "r"(id), "n"(n) : "memory")
template<int N> __device__ __forceinline__ void fence_regs(float (&r)[N]) {
#pragma unroll
    for (int i = 0; i < N; i++) asm volatile("" : "+f"(r[i]) :: "memory");
}
template<int N> __device__ __forceinline__ void fence_regs(uint32_t (&r)[N]) {
#pragma unroll
    for (int i = 0; i < N; i++) asm volatile("" : "+r"(r[i]) :: "memory");
}
__device__ __forceinline__ float ex2(float x) { float y; asm("ex2.approx.ftz.f32 %0, %1;" : "=f"(y) : "f"(x)); return y; }
__device__ __forceinline__ float tanh_fast(float x) { float y; asm("tanh.approx.f32 %0, %1;" : "=f"(y) : "f"(x)); return y; }
__device__ __forceinline__ uint32_t pack_bf16(float lo, float hi) { uint32_t r; asm("cvt.rn.bf16x2.f32 %0, %1, %2;" : "=r"(r) : "f"(hi), "f"(lo)); return r; }
__device__ __forceinline__ uint32_t hfma2(uint32_t a, uint32_t b, uint32_t c) { uint32_t r; asm("fma.rn.bf16x2 %0, %1, %2, %3;" : "=r"(r) : "r"(a), "r"(b), "r"(c)); return r; }
__device__ __forceinline__ float bf_lo(uint32_t v) { return __uint_as_float(v << 16); }
__device__ __forceinline__ float bf_hi(uint32_t v) { return __uint_as_float(v & 0xFFFF0000u); }

template<int N> __device__ __forceinline__ void wgmma_ss(float (&d)[N / 2], uint64_t da, uint64_t db, int scale_d);
template<> __device__ __forceinline__ void wgmma_ss<80>(float (&d)[40], uint64_t da, uint64_t db, int scale_d) {
    asm volatile("{\n.reg .pred p;\nsetp.ne.b32 p, %42, 0;\n"
        "wgmma.mma_async.sync.aligned.m64n80k16.f32.bf16.bf16 {%0,%1,%2,%3,%4,%5,%6,%7,%8,%9,%10,%11,%12,%13,%14,%15,%16,%17,%18,%19,%20,%21,%22,%23,%24,%25,%26,%27,%28,%29,%30,%31,%32,%33,%34,%35,%36,%37,%38,%39}, %40, %41, p, 1, 1, 0, 1;\n}"
        : "+f"(d[0]), "+f"(d[1]), "+f"(d[2]), "+f"(d[3]), "+f"(d[4]), "+f"(d[5]), "+f"(d[6]), "+f"(d[7]), "+f"(d[8]), "+f"(d[9]), "+f"(d[10]), "+f"(d[11]), "+f"(d[12]), "+f"(d[13]), "+f"(d[14]), "+f"(d[15]), "+f"(d[16]), "+f"(d[17]), "+f"(d[18]), "+f"(d[19]), "+f"(d[20]), "+f"(d[21]), "+f"(d[22]), "+f"(d[23]), "+f"(d[24]), "+f"(d[25]), "+f"(d[26]), "+f"(d[27]), "+f"(d[28]), "+f"(d[29]), "+f"(d[30]), "+f"(d[31]), "+f"(d[32]), "+f"(d[33]), "+f"(d[34]), "+f"(d[35]), "+f"(d[36]), "+f"(d[37]), "+f"(d[38]), "+f"(d[39])
        : "l"(da), "l"(db), "r"(scale_d));
}
template<> __device__ __forceinline__ void wgmma_ss<104>(float (&d)[52], uint64_t da, uint64_t db, int scale_d) {
    asm volatile("{\n.reg .pred p;\nsetp.ne.b32 p, %54, 0;\n"
        "wgmma.mma_async.sync.aligned.m64n104k16.f32.bf16.bf16 {%0,%1,%2,%3,%4,%5,%6,%7,%8,%9,%10,%11,%12,%13,%14,%15,%16,%17,%18,%19,%20,%21,%22,%23,%24,%25,%26,%27,%28,%29,%30,%31,%32,%33,%34,%35,%36,%37,%38,%39,%40,%41,%42,%43,%44,%45,%46,%47,%48,%49,%50,%51}, %52, %53, p, 1, 1, 0, 1;\n}"
        : "+f"(d[0]), "+f"(d[1]), "+f"(d[2]), "+f"(d[3]), "+f"(d[4]), "+f"(d[5]), "+f"(d[6]), "+f"(d[7]), "+f"(d[8]), "+f"(d[9]), "+f"(d[10]), "+f"(d[11]), "+f"(d[12]), "+f"(d[13]), "+f"(d[14]), "+f"(d[15]), "+f"(d[16]), "+f"(d[17]), "+f"(d[18]), "+f"(d[19]), "+f"(d[20]), "+f"(d[21]), "+f"(d[22]), "+f"(d[23]), "+f"(d[24]), "+f"(d[25]), "+f"(d[26]), "+f"(d[27]), "+f"(d[28]), "+f"(d[29]), "+f"(d[30]), "+f"(d[31]), "+f"(d[32]), "+f"(d[33]), "+f"(d[34]), "+f"(d[35]), "+f"(d[36]), "+f"(d[37]), "+f"(d[38]), "+f"(d[39]), "+f"(d[40]), "+f"(d[41]), "+f"(d[42]), "+f"(d[43]), "+f"(d[44]), "+f"(d[45]), "+f"(d[46]), "+f"(d[47]), "+f"(d[48]), "+f"(d[49]), "+f"(d[50]), "+f"(d[51])
        : "l"(da), "l"(db), "r"(scale_d));
}
template<> __device__ __forceinline__ void wgmma_ss<112>(float (&d)[56], uint64_t da, uint64_t db, int scale_d) {
    asm volatile("{\n.reg .pred p;\nsetp.ne.b32 p, %58, 0;\n"
        "wgmma.mma_async.sync.aligned.m64n112k16.f32.bf16.bf16 {%0,%1,%2,%3,%4,%5,%6,%7,%8,%9,%10,%11,%12,%13,%14,%15,%16,%17,%18,%19,%20,%21,%22,%23,%24,%25,%26,%27,%28,%29,%30,%31,%32,%33,%34,%35,%36,%37,%38,%39,%40,%41,%42,%43,%44,%45,%46,%47,%48,%49,%50,%51,%52,%53,%54,%55}, %56, %57, p, 1, 1, 0, 1;\n}"
        : "+f"(d[0]), "+f"(d[1]), "+f"(d[2]), "+f"(d[3]), "+f"(d[4]), "+f"(d[5]), "+f"(d[6]), "+f"(d[7]), "+f"(d[8]), "+f"(d[9]), "+f"(d[10]), "+f"(d[11]), "+f"(d[12]), "+f"(d[13]), "+f"(d[14]), "+f"(d[15]), "+f"(d[16]), "+f"(d[17]), "+f"(d[18]), "+f"(d[19]), "+f"(d[20]), "+f"(d[21]), "+f"(d[22]), "+f"(d[23]), "+f"(d[24]), "+f"(d[25]), "+f"(d[26]), "+f"(d[27]), "+f"(d[28]), "+f"(d[29]), "+f"(d[30]), "+f"(d[31]), "+f"(d[32]), "+f"(d[33]), "+f"(d[34]), "+f"(d[35]), "+f"(d[36]), "+f"(d[37]), "+f"(d[38]), "+f"(d[39]), "+f"(d[40]), "+f"(d[41]), "+f"(d[42]), "+f"(d[43]), "+f"(d[44]), "+f"(d[45]), "+f"(d[46]), "+f"(d[47]), "+f"(d[48]), "+f"(d[49]), "+f"(d[50]), "+f"(d[51]), "+f"(d[52]), "+f"(d[53]), "+f"(d[54]), "+f"(d[55])
        : "l"(da), "l"(db), "r"(scale_d));
}
template<> __device__ __forceinline__ void wgmma_ss<120>(float (&d)[60], uint64_t da, uint64_t db, int scale_d) {
    asm volatile("{\n.reg .pred p;\nsetp.ne.b32 p, %62, 0;\n"
        "wgmma.mma_async.sync.aligned.m64n120k16.f32.bf16.bf16 {%0,%1,%2,%3,%4,%5,%6,%7,%8,%9,%10,%11,%12,%13,%14,%15,%16,%17,%18,%19,%20,%21,%22,%23,%24,%25,%26,%27,%28,%29,%30,%31,%32,%33,%34,%35,%36,%37,%38,%39,%40,%41,%42,%43,%44,%45,%46,%47,%48,%49,%50,%51,%52,%53,%54,%55,%56,%57,%58,%59}, %60, %61, p, 1, 1, 0, 1;\n}"
        : "+f"(d[0]), "+f"(d[1]), "+f"(d[2]), "+f"(d[3]), "+f"(d[4]), "+f"(d[5]), "+f"(d[6]), "+f"(d[7]), "+f"(d[8]), "+f"(d[9]), "+f"(d[10]), "+f"(d[11]), "+f"(d[12]), "+f"(d[13]), "+f"(d[14]), "+f"(d[15]), "+f"(d[16]), "+f"(d[17]), "+f"(d[18]), "+f"(d[19]), "+f"(d[20]), "+f"(d[21]), "+f"(d[22]), "+f"(d[23]), "+f"(d[24]), "+f"(d[25]), "+f"(d[26]), "+f"(d[27]), "+f"(d[28]), "+f"(d[29]), "+f"(d[30]), "+f"(d[31]), "+f"(d[32]), "+f"(d[33]), "+f"(d[34]), "+f"(d[35]), "+f"(d[36]), "+f"(d[37]), "+f"(d[38]), "+f"(d[39]), "+f"(d[40]), "+f"(d[41]), "+f"(d[42]), "+f"(d[43]), "+f"(d[44]), "+f"(d[45]), "+f"(d[46]), "+f"(d[47]), "+f"(d[48]), "+f"(d[49]), "+f"(d[50]), "+f"(d[51]), "+f"(d[52]), "+f"(d[53]), "+f"(d[54]), "+f"(d[55]), "+f"(d[56]), "+f"(d[57]), "+f"(d[58]), "+f"(d[59])
        : "l"(da), "l"(db), "r"(scale_d));
}
template<int SCALE_D> __device__ __forceinline__ void wgmma_qk(float (&d)[32], uint32_t a0, uint32_t a1, uint32_t a2, uint32_t a3, uint64_t db) {
    asm volatile("wgmma.mma_async.sync.aligned.m64n64k16.f32.bf16.bf16 {%0,%1,%2,%3,%4,%5,%6,%7,%8,%9,%10,%11,%12,%13,%14,%15,%16,%17,%18,%19,%20,%21,%22,%23,%24,%25,%26,%27,%28,%29,%30,%31}, {%32,%33,%34,%35}, %36, %37, 1, 1, 0;"
        : "+f"(d[0]), "+f"(d[1]), "+f"(d[2]), "+f"(d[3]), "+f"(d[4]), "+f"(d[5]), "+f"(d[6]), "+f"(d[7]), "+f"(d[8]), "+f"(d[9]), "+f"(d[10]), "+f"(d[11]), "+f"(d[12]), "+f"(d[13]), "+f"(d[14]), "+f"(d[15]), "+f"(d[16]), "+f"(d[17]), "+f"(d[18]), "+f"(d[19]), "+f"(d[20]), "+f"(d[21]), "+f"(d[22]), "+f"(d[23]), "+f"(d[24]), "+f"(d[25]), "+f"(d[26]), "+f"(d[27]), "+f"(d[28]), "+f"(d[29]), "+f"(d[30]), "+f"(d[31])
        : "r"(a0), "r"(a1), "r"(a2), "r"(a3), "l"(db), "n"(SCALE_D));
}
template<int SCALE_D> __device__ __forceinline__ void wgmma_pv(float (&d)[12], uint32_t a0, uint32_t a1, uint32_t a2, uint32_t a3, uint64_t db) {
    asm volatile("wgmma.mma_async.sync.aligned.m64n24k16.f32.bf16.bf16 {%0,%1,%2,%3,%4,%5,%6,%7,%8,%9,%10,%11}, {%12,%13,%14,%15}, %16, %17, 1, 1, 1;"
        : "+f"(d[0]), "+f"(d[1]), "+f"(d[2]), "+f"(d[3]), "+f"(d[4]), "+f"(d[5]), "+f"(d[6]), "+f"(d[7]), "+f"(d[8]), "+f"(d[9]), "+f"(d[10]), "+f"(d[11])
        : "r"(a0), "r"(a1), "r"(a2), "r"(a3), "l"(db), "n"(SCALE_D));
}

__device__ __forceinline__ void mbar_arrive_n(uint32_t bar, uint32_t n) { asm volatile("mbarrier.arrive.shared::cta.b64 _, [%0], %1;" :: "r"(bar), "r"(n) : "memory"); }
__device__ __forceinline__ uint32_t ld_acquire(const uint32_t* p) { uint32_t v; asm volatile("ld.acquire.gpu.global.u32 %0, [%1];" : "=r"(v) : "l"(p) : "memory"); return v; }
__device__ __forceinline__ void flag_signal(uint32_t* p) { asm volatile("red.release.gpu.global.add.u32 [%0], 1;" :: "l"(p) : "memory"); }
__device__ __forceinline__ uint32_t ld_relaxed(const uint32_t* p) { uint32_t v; asm volatile("ld.relaxed.gpu.global.u32 %0, [%1];" : "=r"(v) : "l"(p) : "memory"); return v; }
__device__ __forceinline__ void acquire_fence() { asm volatile("fence.acq_rel.gpu;" ::: "memory"); }
template<int SLEEP = 64>
__device__ __forceinline__ void flag_wait(const uint32_t* p, uint32_t target) {
    int spins = 0;
    while ((int)(ld_relaxed(p) - target) < 0) { __nanosleep(SLEEP); if (++spins > (1 << 21)) __trap(); }
    (void)ld_acquire(p);
}
template<int SLEEP>
__device__ __forceinline__ void flag_wait_warp(const uint32_t* p, uint32_t target) {
    int spins = 0;
    while (__any_sync(0xffffffffu, (int)(ld_relaxed(p) - target) < 0)) { __nanosleep(SLEEP); if (++spins > (1 << 21)) __trap(); }
    (void)ld_acquire(p);
}
__device__ __forceinline__ void proxy_fence() { asm volatile("fence.proxy.async;" ::: "memory"); }
__device__ __forceinline__ void bulk_commit_wait() {
    asm volatile("cp.async.bulk.commit_group;" ::: "memory");
    asm volatile("cp.async.bulk.wait_group 0;" ::: "memory");
}

constexpr int ASLOTS = 6, BSLOTS = 4;
constexpr uint32_t B_SLOT = 32768, OFF_A = BSLOTS * B_SLOT, A_RING = ASLOTS * 8192, OFF_KV = B_SLOT, OFF_CS = OFF_A + 2 * A_RING;
constexpr uint32_t OFF_BAR = OFF_CS + 456 * 4;
constexpr uint32_t BAR_FULLA = OFF_BAR, BAR_EMPTYA = BAR_FULLA + 8 * 2 * ASLOTS, BAR_FULLB = BAR_EMPTYA + 8 * 2 * ASLOTS, BAR_EMPTYB = BAR_FULLB + 8 * BSLOTS;
constexpr uint32_t BAR_KV = BAR_EMPTYB + 8 * BSLOTS, BAR_KMAX = BAR_KV + 8 * 16, BAR_Q = BAR_KMAX + 8, BAR_AUX = BAR_Q + 8, BAR_QDONE = BAR_AUX + 8, BAR_SCR = BAR_QDONE + 8, BAR_ST = BAR_SCR + 8, OFF_KMAX = BAR_ST + 8, SMEM_BYTES = OFF_KMAX + 16;
__device__ __forceinline__ uint32_t bslot_off(uint32_t s) { return ((s + 3) & 3) * B_SLOT; }

struct Ring {
    uint32_t slot, phase;
    template<int N> __device__ __forceinline__ void next() { if (++slot == N) { slot = 0; phase ^= 1; } }
    template<int N> __device__ __forceinline__ void skip(int n) { slot += n; while (slot >= N) { slot -= N; phase ^= 1; } }
    template<int N> __device__ __forceinline__ void set(int idx) { slot = idx % N; phase = (idx / N) & 1; }
};
constexpr int A_PER_LAYER = 63, B_PER_LAYER = 36;
__device__ __forceinline__ uint64_t desc_add(uint64_t d, uint32_t off) {
    uint32_t lo = (uint32_t)d + off, hi = (uint32_t)(d >> 32);
    uint64_t r; asm("mov.b64 %0, {%1, %2};" : "=l"(r) : "r"(lo), "r"(hi)); return r;
}

struct Maps { CUtensorMap x, wqkv, st_out; };

template<int NW, typename Hook>
__device__ __forceinline__ void gemm_loop(float (&acc)[NW / 2], uint32_t sbase, int r, int a0, int b0, uint64_t bdesc, uint32_t bstep, int lane, bool a_swz, Hook hook) {
    const uint64_t adesc = a_swz ? mkdesc(sbase + OFF_A + r * A_RING, 16, 1024, 1) : mkdesc(sbase + OFF_A + r * A_RING, 1024, 128, 0);
    const uint32_t astep = a_swz ? 2 : 128;
    Ring ra, rb;
    ra.set<ASLOTS>(a0); rb.set<BSLOTS>(b0);
#pragma unroll
    for (int i = 0; i < NW / 2; i++) acc[i] = 0.f;
    fence_regs(acc);
#pragma unroll 1
    for (int kb = 0; kb < 10; kb++) {
        mbar_wait(sbase + BAR_FULLA + 8 * (r * ASLOTS + ra.slot), ra.phase);
        mbar_wait(sbase + BAR_FULLB + 8 * rb.slot, rb.phase);
        const uint32_t oa = ra.slot * (8192 >> 4), ob = bslot_off(rb.slot) >> 4;
        WG_FENCE();
#pragma unroll
        for (int k = 0; k < 4; k++) wgmma_ss<NW>(acc, desc_add(adesc, oa + k * astep), desc_add(bdesc, ob + k * bstep), 1);
        WG_COMMIT();
        hook(kb);
        WG_WAIT(0);
        if (lane == 0) {
            if (kb + ASLOTS < 10) mbar_arrive_n(sbase + BAR_EMPTYA + 8 * (r * ASLOTS + ra.slot), 2);
            mbar_arrive(sbase + BAR_EMPTYB + 8 * rb.slot);
        }
        ra.next<ASLOTS>();
        rb.next<BSLOTS>();
    }
    fence_regs(acc);
}
__device__ __forceinline__ void res_loop(float (&acc)[40], int KB, uint32_t sbase, int r, int h, int a0, int b0, int lane) {
    const uint64_t adesc = mkdesc(sbase + OFF_A + r * A_RING, 1024, 128, 0), bdesc = mkdesc(sbase, 1280, 128, 0);
#pragma unroll
    for (int i = 0; i < 40; i++) acc[i] = 0.f;
    fence_regs(acc);
    Ring ra, rb;
    ra.set<ASLOTS>(a0 + h); rb.set<BSLOTS>(b0);
    int kin = h;
    bool newb = true;
#pragma unroll 1
    for (int kb = h; kb < KB; kb += 2) {
        mbar_wait(sbase + BAR_FULLA + 8 * (r * ASLOTS + ra.slot), ra.phase);
        if (newb) mbar_wait(sbase + BAR_FULLB + 8 * rb.slot, rb.phase);
        const uint32_t oa = ra.slot * (8192 >> 4), ob = (bslot_off(rb.slot) >> 4) + kin * (10240 >> 4);
        WG_FENCE();
#pragma unroll
        for (int k = 0; k < 4; k++) wgmma_ss<80>(acc, desc_add(adesc, oa + k * 128), desc_add(bdesc, ob + k * (2560 >> 4)), 1);
        WG_COMMIT();
        kin += 2;
        newb = kin >= 3;
        WG_WAIT(0);
        if (lane == 0) {
            if (kb + ASLOTS < KB) mbar_arrive_n(sbase + BAR_EMPTYA + 8 * (r * ASLOTS + ra.slot), 4);
            if (newb || kb + 2 >= KB) mbar_arrive(sbase + BAR_EMPTYB + 8 * rb.slot);
        }
        ra.next<ASLOTS>(); ra.next<ASLOTS>();
        if (newb) { kin -= 3; rb.next<BSLOTS>(); }
    }
    fence_regs(acc);
    if (lane == 0 && KB == 10 && h == 0) mbar_arrive(sbase + BAR_EMPTYB + 8 * rb.slot);
}
__device__ __forceinline__ void release_ring(uint32_t sbase, int r, uint32_t cnt) {
#pragma unroll
    for (int s = 0; s < ASLOTS; s++) mbar_arrive_n(sbase + BAR_EMPTYA + 8 * (r * ASLOTS + s), cnt);
}
struct StatRegs {
    float4 v[4];
    float2 st0, st1;
    __device__ __forceinline__ void clear() { v[0] = v[1] = v[2] = v[3] = make_float4(0.f, 0.f, 0.f, 0.f); st0 = st1 = make_float2(0.f, 0.f); }
    __device__ __forceinline__ void load(const float4* p  , int lrow, int c) {
        v[0] = __ldcg(p + c * 64 + lrow); v[1] = __ldcg(p + (c + 4) * 64 + lrow);
        v[2] = __ldcg(p + c * 64 + lrow + 8); v[3] = __ldcg(p + (c + 4) * 64 + lrow + 8);
    }
    static __device__ __forceinline__ float2 fin(const float4 a, const float4 b) {
        float s = (a.x + a.z) + (b.x + b.z), q = (a.y + a.w) + (b.y + b.w);
        s += __shfl_xor_sync(0xffffffffu, s, 1); q += __shfl_xor_sync(0xffffffffu, q, 1);
        s += __shfl_xor_sync(0xffffffffu, s, 2); q += __shfl_xor_sync(0xffffffffu, q, 2);
        const float mean = s * (1.f / DM);
        const float rstd = rsqrtf(fmaxf(q * (1.f / DM) - mean * mean, 0.f) + 1e-5f);
        return make_float2(rstd, -mean * rstd);
    }
    __device__ __forceinline__ void finish() { st0 = fin(v[0], v[1]); st1 = fin(v[2], v[3]); }
};
__device__ __forceinline__ void load_cs(float* cs_s, int col0, int n, int lane) {
#pragma unroll 1
    for (int i = lane * 4; i < n; i += 128) {
        float4 v[16];
#pragma unroll
        for (int j = 0; j < 16; j++) v[j] = __ldcg((const float4*)&g_cs[j][col0 + i]);
        float4 a = v[0];
#pragma unroll
        for (int j = 1; j < 16; j++) { a.x += v[j].x; a.y += v[j].y; a.z += v[j].z; a.w += v[j].w; }
        *(float4*)(cs_s + i) = a;
    }
}
template<int NB>
__device__ __forceinline__ void stage_tile(const uint32_t (&ov)[2 * NB], uint32_t stg, int warp, int lane) {
    const uint32_t addr = stg + (lane >> 4) * 1024 + (warp * 16 + (lane & 15)) * 16;
#pragma unroll
    for (int j = 0; j + 1 < NB; j += 2)
        asm volatile("stmatrix.sync.aligned.m8n8.x4.shared.b16 [%0], {%1, %2, %3, %4};"
            :: "r"(addr + j * 1024), "r"(ov[2 * j]), "r"(ov[2 * j + 1]), "r"(ov[2 * j + 2]), "r"(ov[2 * j + 3]) : "memory");
    if (NB & 1)
        asm volatile("stmatrix.sync.aligned.m8n8.x2.shared.b16 [%0], {%1, %2};" :: "r"(addr + (NB - 1) * 1024), "r"(ov[2 * NB - 2]), "r"(ov[2 * NB - 1]) : "memory");
}
template<int NB>
__device__ __forceinline__ void stage_tile_swz(const uint32_t (&ov)[2 * NB], uint32_t stg, int blk0, int warp, int lane) {
    const int srow = warp * 16 + (lane & 15);
#pragma unroll
    for (int j = 0; j < NB; j += 2) {
        const int blk = blk0 + j + (j + 1 < NB ? (lane >> 4) : 0);
        const uint32_t addr = stg + (blk >> 3) * 8192 + srow * 128 + (((blk & 7) ^ (srow & 7)) << 4);
        if (j + 1 < NB)
            asm volatile("stmatrix.sync.aligned.m8n8.x4.shared.b16 [%0], {%1, %2, %3, %4};"
                :: "r"(addr), "r"(ov[2 * j]), "r"(ov[2 * j + 1]), "r"(ov[(2 * j + 2) % (2 * NB)]), "r"(ov[(2 * j + 3) % (2 * NB)]) : "memory");
        else
            asm volatile("stmatrix.sync.aligned.m8n8.x2.shared.b16 [%0], {%1, %2};" :: "r"(addr), "r"(ov[2 * j]), "r"(ov[2 * j + 1]) : "memory");
    }
}
template<int NW>
__device__ __forceinline__ void w1_phase(uint32_t sbase, const float* cs_s, int r, int blk0, int a0, int b0, const float4* stats, int warp) {
    float acc[NW / 2];
    StatRegs sv; sv.clear();
    { THREAD_IDS;
    gemm_loop<NW>(acc, sbase, r, a0, b0, mkdesc(sbase + blk0 * 128, 27 * 128, 128, 0), (2 * 27 * 128) >> 4, lane, false,
        [&](int kb) { if (kb == 1) sv.load(stats, lrow, c); if (kb == 6) sv.finish(); });
    }
    THREAD_IDS;
    float2 st0 = sv.st0, st1 = sv.st1;
    st0.x *= 0.5f; st0.y *= 0.5f; st1.x *= 0.5f; st1.y *= 0.5f;
    mbar_wait(sbase + BAR_AUX, 1);
    const float2* cs = (const float2*)(cs_s + 240 + blk0 * 8) + c;
    uint32_t ov[NW / 4];
#pragma unroll
    for (int j = 0; j < NW / 8; j++) {
        const float2 cv = cs[j * 4];
        const float h0 = fmaf(acc[4 * j], st0.x, st0.y * cv.x), h1 = fmaf(acc[4 * j + 1], st0.x, st0.y * cv.y);
        const float h2 = fmaf(acc[4 * j + 2], st1.x, st1.y * cv.x), h3 = fmaf(acc[4 * j + 3], st1.x, st1.y * cv.y);
        ov[2 * j] = pack_bf16(fmaf(h0, tanh_fast(h0), h0), fmaf(h1, tanh_fast(h1), h1));
        ov[2 * j + 1] = pack_bf16(fmaf(h2, tanh_fast(h2), h2), fmaf(h3, tanh_fast(h3), h3));
    }
    NAMED_BAR(1 + r, 256);
    stage_tile<NW / 8>(ov, sbase + OFF_A + r * A_RING + blk0 * 1024, warp, lane);
}

__device__ __forceinline__ uint32_t poly_pair(float y0, float y1, uint32_t mmask) {
    const uint32_t L = __byte_perm(__float_as_uint(y0), __float_as_uint(y1), 0x6521);
    uint32_t U, Y;
    asm("lop3.b32 %0, %1, %2, 0x3F003F00, 0xEA;" : "=r"(U) : "r"(L), "r"(mmask));
    asm("lop3.b32 %0, %1, %2, 0x00010001, 0xBA;" : "=r"(Y) : "r"(L), "r"(mmask));
    return hfma2(L, U, Y);
}
__device__ __forceinline__ void exp_tile(float (&s)[32], uint32_t (&p)[16], uint32_t mmask) {
    fence_regs(s);
#pragma unroll
    for (int b = 0; b < 8; b++) {
        if ((POLY_MASK >> b) & 1) {
            p[2 * b] = poly_pair(s[4 * b], s[4 * b + 1], mmask);
            p[2 * b + 1] = poly_pair(s[4 * b + 2], s[4 * b + 3], mmask);
        } else {
            p[2 * b] = pack_bf16(ex2(s[4 * b]), ex2(s[4 * b + 1]));
            p[2 * b + 1] = pack_bf16(ex2(s[4 * b + 2]), ex2(s[4 * b + 3]));
        }
    }
    fence_regs(p);
}
__device__ __forceinline__ void mma16816(float (&d)[4], uint32_t a0, uint32_t a1, uint32_t a2, uint32_t a3, uint32_t b0, uint32_t b1) {
    asm volatile("mma.sync.aligned.m16n8k16.row.col.f32.bf16.bf16.f32 {%0,%1,%2,%3}, {%4,%5,%6,%7}, {%8,%9}, {%0,%1,%2,%3};"
        : "+f"(d[0]), "+f"(d[1]), "+f"(d[2]), "+f"(d[3]) : "r"(a0), "r"(a1), "r"(a2), "r"(a3), "r"(b0), "r"(b1));
}
__device__ __forceinline__ uint32_t movtrans(uint32_t v) { uint32_t r; asm volatile("movmatrix.sync.aligned.m8n8.trans.b16 %0, %1;" : "=r"(r) : "r"(v)); return r; }
__device__ __forceinline__ void attn_rows_safe(float (&o)[12], const uint32_t* gq, const uint8_t* qkvx, int head, int lane) {
    const int c = lane & 3;
    const uint32_t q0 = __ldcg(gq), q1 = __ldcg(gq + 96), q2 = __ldcg(gq + 32), q3 = __ldcg(gq + 128);
    const uint32_t q4 = c < 2 ? __ldcg(gq + 64) : 0u, q5 = c < 2 ? __ldcg(gq + 160) : 0u;
    const uint32_t* gk = (const uint32_t*)(qkvx + (size_t)(NH + head) * HEAD_BYTES) + lane;
    const uint32_t* gv = (const uint32_t*)(qkvx + (size_t)(2 * NH + head) * HEAD_BYTES) + lane;
    float oo[3][4];
#pragma unroll
    for (int j = 0; j < 3; j++) { oo[j][0] = oo[j][1] = oo[j][2] = oo[j][3] = 0.f; }
    float m0 = -INFINITY, m1 = -INFINITY;
#pragma unroll 1
    for (int t = 0; t < SEQ / 16; t++) {
        float s[2][4];
#pragma unroll
        for (int b = 0; b < 2; b++) {
            const uint32_t* kp = gk + (t * 2 + b) * 96;
            const uint32_t k0 = __ldcg(kp), k1 = __ldcg(kp + 32), k2 = __ldcg(kp + 64);
            s[b][0] = s[b][1] = s[b][2] = s[b][3] = 0.f;
            mma16816(s[b], q0, q1, q2, q3, k0, k1);
            mma16816(s[b], q4, q5, 0u, 0u, k2, 0u);
            const float f = (POLY_MASK >> ((t * 2 + b) & 7)) & 1 ? 0.5f : 1.f;
            s[b][0] *= f; s[b][1] *= f; s[b][2] *= f; s[b][3] *= f;
        }
        float n0 = fmaxf(fmaxf(m0, fmaxf(s[0][0], s[0][1])), fmaxf(s[1][0], s[1][1]));
        float n1 = fmaxf(fmaxf(m1, fmaxf(s[0][2], s[0][3])), fmaxf(s[1][2], s[1][3]));
        n0 = fmaxf(n0, __shfl_xor_sync(0xffffffffu, n0, 1)); n0 = fmaxf(n0, __shfl_xor_sync(0xffffffffu, n0, 2));
        n1 = fmaxf(n1, __shfl_xor_sync(0xffffffffu, n1, 1)); n1 = fmaxf(n1, __shfl_xor_sync(0xffffffffu, n1, 2));
        const float a0 = ex2(m0 - n0), a1 = ex2(m1 - n1);
        m0 = n0; m1 = n1;
        const uint32_t p0 = pack_bf16(ex2(s[0][0] - m0), ex2(s[0][1] - m0)), p1 = pack_bf16(ex2(s[0][2] - m1), ex2(s[0][3] - m1));
        const uint32_t p2 = pack_bf16(ex2(s[1][0] - m0), ex2(s[1][1] - m0)), p3 = pack_bf16(ex2(s[1][2] - m1), ex2(s[1][3] - m1));
#pragma unroll
        for (int j = 0; j < 3; j++) {
            const uint32_t v0 = movtrans(__ldcg(gv + (t * 2) * 96 + j * 32)), v1 = movtrans(__ldcg(gv + (t * 2 + 1) * 96 + j * 32));
            oo[j][0] *= a0; oo[j][1] *= a0; oo[j][2] *= a1; oo[j][3] *= a1;
            mma16816(oo[j], p0, p1, p2, p3, v0, v1);
        }
    }
#pragma unroll
    for (int j = 0; j < 3; j++) { o[4 * j] = oo[j][0]; o[4 * j + 1] = oo[j][1]; o[4 * j + 2] = oo[j][2]; o[4 * j + 3] = oo[j][3]; }
}
#define ATT_QK(off) do { wgmma_qk<0>(s0, q0, q1, q2, q3, desc_add(dK0, (off))); wgmma_qk<1>(s0, q4, q5, zero, zero, desc_add(dK1, (off))); } while (0)
#define ATT_PV(off) do { _Pragma("unroll") for (int j = 0; j < 4; j++) wgmma_pv<1>(o, p0[4 * j], p0[4 * j + 1], p0[4 * j + 2], p0[4 * j + 3], desc_add(dV, (off) + ((j * 768) >> 4))); } while (0)

constexpr int PK_STAGES = 4, PK_SLOT = 30720, PK_OUT = PK_STAGES * PK_SLOT, PK_BAR = PK_OUT + 3 * PK_SLOT;
template<int BN, int K, int R>
__device__ __forceinline__ void pack_weight(const bf16* __restrict__ w, uint8_t* __restrict__ dst, uint8_t* smem, uint32_t sbase, int& seq, int tid) {
    constexpr int NG = BN / 8, N8 = 8 * NG, P = N8 * 16, NST = K / R / NHELP;
    static_assert(R * P <= PK_SLOT && (K / R) % NHELP == 0, "");
    const uint32_t bars = sbase + PK_BAR;
    auto issue = [&](int i) {
        const int sl = (seq + i) % PK_STAGES;
        mbar_expect(bars + 8 * sl, R * P);
        bulk_g2s(sbase + sl * PK_SLOT, (const char*)w + (size_t)(i * NHELP + blockIdx.x) * R * P, R * P, bars + 8 * sl);
    };
    const bool storer = (tid & 31) == 0 && tid < 256;
    if (tid == 256) for (int i = 0; i < PK_STAGES && i < NST; i++) issue(i);
    constexpr int NE = (R * N8 + NTHREADS - 1) / NTHREADS;
    int so[NE], dofs[NE];
#pragma unroll
    for (int j = 0; j < NE; j++) {
        const int e = tid + j * NTHREADS;
        const int kr = e & 7, u = e >> 3, kg = u / N8, v = u % N8, n8 = (v & ~7) | ((v + kr) & 7), nt = n8 / NG, ng = n8 % NG;
        so[j] = e < R * N8 ? (kg * 8 + kr) * P + n8 * 16 : -1;
        dofs[j] = ((nt * (R / 8) + kg) * NG + ng) * 128 + kr * 16;
    }
#pragma unroll 1
    for (int i = 0; i < NST; i++) {
        const int sl = (seq + i) % PK_STAGES, ob = PK_OUT + ((seq + i) % 3) * PK_SLOT;
        mbar_wait(bars + 8 * sl, ((seq + i) / PK_STAGES) & 1);
        uint4 v[NE];
#pragma unroll
        for (int j = 0; j < NE; j++) if (so[j] >= 0) v[j] = *(const uint4*)(smem + sl * PK_SLOT + so[j]);
#pragma unroll
        for (int j = 0; j < NE; j++) if (so[j] >= 0) *(uint4*)(smem + ob + dofs[j]) = v[j];
        asm volatile("fence.proxy.async.shared::cta;" ::: "memory");
        if (storer) asm volatile("cp.async.bulk.wait_group.read 1;" ::: "memory");
        __syncthreads();
        if (tid == 256 && i + PK_STAGES < NST) issue(i + PK_STAGES);
        if (storer) {
            const int kg0 = (i * NHELP + blockIdx.x) * (R / 8), nt = tid >> 5;
            bulk_s2g(dst + ((size_t)nt * (K / 8) + kg0) * NG * 128, sbase + ob + nt * (R / 8) * NG * 128, (R / 8) * NG * 128);
            asm volatile("cp.async.bulk.commit_group;" ::: "memory");
        }
    }
    seq += NST;
    if (storer) asm volatile("cp.async.bulk.wait_group 0;" ::: "memory");
    __syncthreads();
}
__device__ __forceinline__ void colsum40(const bf16* __restrict__ p, int ld, float* out) {
    float a[8];
#pragma unroll
    for (int j = 0; j < 8; j++) a[j] = 0.f;
#pragma unroll 1
    for (int i0 = 0; i0 < 40; i0 += 20) {
        uint4 v[20];
#pragma unroll
        for (int i = 0; i < 20; i++) v[i] = __ldg((const uint4*)(p + (size_t)(i0 + i) * ld));
#pragma unroll
        for (int i = 0; i < 20; i++) {
            a[0] += bf_lo(v[i].x); a[1] += bf_hi(v[i].x); a[2] += bf_lo(v[i].y); a[3] += bf_hi(v[i].y);
            a[4] += bf_lo(v[i].z); a[5] += bf_hi(v[i].z); a[6] += bf_lo(v[i].w); a[7] += bf_hi(v[i].w);
        }
    }
    *(float4*)out = make_float4(a[0], a[1], a[2], a[3]);
    *(float4*)(out + 4) = make_float4(a[4], a[5], a[6], a[7]);
}
#define POLL_NS 100
#define SIG_RELAXED 1
#define RD_FENCE 0
__device__ __forceinline__ void flag_signal_bulk(uint32_t* p) {
    asm volatile("red.relaxed.gpu.global.add.u32 [%0], 1;" :: "l"(p) : "memory");
}
__device__ __forceinline__ void reader_fence() {
}

__device__ __forceinline__ bool poll_flags(const uint32_t* myflag, uint32_t target, uint32_t need, uint32_t& seen, int lane) {
    if ((seen & need) == need) return false;
    int spins = 0;
    while (true) {
        bool ready = (seen >> lane) & 1;
        if (!ready && myflag) { ready = (int)(ld_relaxed(myflag) - target) >= 0; if (ready) (void)ld_acquire(myflag); }
        seen = __ballot_sync(0xffffffffu, ready);
        if ((seen & need) == need) return true;
        __nanosleep(POLL_NS);
        if (++spins > (1 << 21)) __trap();
    }
}

__global__ void __launch_bounds__(NTHREADS, 1) fused_kernel(const __grid_constant__ Maps maps, const bf16* __restrict__ x, const bf16* __restrict__ wqkv,
                                                            const bf16* __restrict__ wo, const bf16* __restrict__ w1, const bf16* __restrict__ w2) {
    extern __shared__ __align__(1024) uint8_t smem[];
    const uint32_t sbase = smem_u32(smem);
    const int tid = threadIdx.x, warp_id = __shfl_sync(0xffffffffu, tid >> 5, 0), lane = tid & 31;
    Flags* const F = &g_flags;

    if (blockIdx.x < NHELP) {
        if (tid == 0) {
            for (int i = 0; i < PK_STAGES; i++) mbar_init(sbase + PK_BAR + 8 * i, 1);
            asm volatile("fence.mbarrier_init.release.cluster;" ::: "memory");
        }
        __syncthreads();
        int seq = 0;
        pack_weight<80, DM, 16>(wo, g_wo_p, smem, sbase, seq, tid);
        if (tid == 0) { __threadfence(); flag_signal(F->pack[0]); TS(15, 0); }
        pack_weight<216, DM, 8>(w1, g_w1_p, smem, sbase, seq, tid);
        if (tid == 0) { __threadfence(); flag_signal(F->pack[1]); TS(15, 1); }
        pack_weight<80, FF, 24>(w2, g_w2_p, smem, sbase, seq, tid);
        if (tid == 0) { __threadfence(); flag_signal(F->pack[2]); TS(15, 2); }
        pack_weight<240, DM, 8>(wqkv, g_wqkv_p, smem, sbase, seq, tid);
        if (tid == 0) { __threadfence(); flag_signal(F->pack[3]); TS(15, 3); }
        return;
    }
    const int w = blockIdx.x - NHELP;
    const int mt = w >> 3, nt = w & 7;
    const int head = w >> 2, quarter = w & 3;
    if (tid == 544) asm volatile("cp.async.bulk.prefetch.L2.global [%0], 20480;" :: "l"((const char*)x + (size_t)w * 20480) : "memory");
    if (tid == 576) asm volatile("cp.async.bulk.prefetch.L2.global [%0], 19200;" :: "l"((const char*)wqkv + (size_t)w * 19200) : "memory");
    uint4 pre[5];
    if (warp_id < 8) {
        const bf16* p = wqkv + (size_t)((mt >> 1) * 80 + warp_id * 10 + (lane >> 4) * 5) * (3 * DM) + nt * 240 + (mt & 1) * 120 + ((lane & 15) < 15 ? (lane & 15) : 0) * 8;
#pragma unroll
        for (int i = 0; i < 5; i++) pre[i] = __ldg((const uint4*)(p + (size_t)i * (3 * DM)));
    } else if (warp_id < 16) {
        const bf16* p = x + (size_t)(mt * 128 + (lane >> 4) * 64 + nt * 8 + warp_id - 8) * DM + (lane & 15) * 8;
#pragma unroll
        for (int i = 0; i < 5; i++) pre[i] = __ldg((const uint4*)(p + i * 128));
    }
    if (warp_id >= 16 && elect_one()) {
        if (warp_id < 18) {
#pragma unroll
            for (int i = 0; i < ASLOTS; i++) { mbar_init(sbase + BAR_FULLA + 8 * ((warp_id - 16) * ASLOTS + i), 1); mbar_init(sbase + BAR_EMPTYA + 8 * ((warp_id - 16) * ASLOTS + i), 16); }
        } else if (warp_id == 18) {
            TS(0, 0);
            if (sbase & 1023) __trap();
#pragma unroll
            for (int i = 0; i < BSLOTS; i++) { mbar_init(sbase + BAR_FULLB + 8 * i, 1); mbar_init(sbase + BAR_EMPTYB + 8 * i, 16); }
            mbar_init(sbase + BAR_KMAX, 1); mbar_init(sbase + BAR_Q, 1); mbar_init(sbase + BAR_AUX, 1);
            mbar_init(sbase + BAR_QDONE, 16); mbar_init(sbase + BAR_SCR, 1); mbar_init(sbase + BAR_ST, 1);
        } else {
#pragma unroll
            for (int i = 0; i < 16; i++) mbar_init(sbase + BAR_KV + 8 * i, 1);
        }
        asm volatile("fence.mbarrier_init.release.cluster;" ::: "memory");
    }
    __syncthreads();

    if (warp_id >= 16) {
        auto load_kv = [&](int layer, int t0, int n, uint32_t epoch) {
            const uint8_t* gK = g_qkvx[layer] + (size_t)(NH + head) * HEAD_BYTES;
            const uint8_t* gV = g_qkvx[layer] + (size_t)(2 * NH + head) * HEAD_BYTES;
            const uint32_t* myflag = lane < 4 * n ? &F->qkv[layer][((lane & 2 ? 2 * NH : NH) + head) / 6][(t0 + (lane >> 2)) * 2 + (lane & 1)] : nullptr;
            uint32_t seen = 0;
#pragma unroll 1
            for (int i = 0; i < n; i++) {
                const bool fresh = poll_flags(myflag, epoch, 0xFu << (4 * i), seen, lane);
                if (fresh) reader_fence();
                if (elect_one()) {
                    const int t = t0 + i;
                    mbar_expect(sbase + BAR_KV + 8 * t, 12288);
                    bulk_g2s(sbase + OFF_KV + t * 12288, gK + t * 6144, 6144, sbase + BAR_KV + 8 * t);
                    bulk_g2s(sbase + OFF_KV + t * 12288 + 6144, gV + t * 6144, 6144, sbase + BAR_KV + 8 * t);
                }
                __syncwarp();
            }
        };
        if (warp_id == 19) {
            float* cs_s = (float*)(smem + OFF_CS);
            const uint32_t epoch = __ldcg(F->epoch) + 1;
            {
                if (lane == 0) TS(0, 3);
                NAMED_BAR(7, 544);
                if (lane == 0) TS(0, 4);
                const float4* scr = (const float4*)(smem + OFF_A + 2 * A_RING - 8192);
                if (lane < 30) {
                    float4 a = scr[lane];
#pragma unroll
                    for (int i = 1; i < 16; i++) { const float4 u = scr[i * 30 + lane]; a.x += u.x; a.y += u.y; a.z += u.z; a.w += u.w; }
                    *(float4*)(cs_s + lane * 4) = a;
                }
                asm volatile("fence.proxy.async.shared::cta;" ::: "memory");
                __syncwarp();
                if (lane == 0) {
                    TS(0, 5);
                    bulk_s2g(&g_cs[mt >> 1][nt * 240 + (mt & 1) * 120], sbase + OFF_CS, 480);
                    bulk_s2g(&g_stats[0][mt * 2][0][nt * 8], sbase + OFF_A + 2 * A_RING - 8192 + 7680, 128);
                    bulk_s2g(&g_stats[0][mt * 2 + 1][0][nt * 8], sbase + OFF_A + 2 * A_RING - 8192 + 7680 + 128, 128);
                    bulk_commit_wait();
                    flag_signal_bulk(F->cs[0][nt]);
                    flag_signal_bulk(F->st0[mt]);
                    mbar_arrive(sbase + BAR_SCR);
                }
                __syncwarp();
                if (lane == 0) TS(0, 1);
                uint32_t seen = 0;
                poll_flags(lane == 0 ? F->cs[0][nt] : (lane == 1 ? F->st0[mt] : nullptr), epoch * (lane == 0 ? 16 : 8), 3u, seen, lane);
                if (lane == 0) { mbar_arrive(sbase + BAR_ST); TS(0, 6); }
                if (lane < 30) {
                    float4 v[16];
#pragma unroll
                    for (int j = 0; j < 16; j++) v[j] = __ldcg((const float4*)&g_cs[j & 7][nt * 240 + (j >> 3) * 120 + lane * 4]);
#pragma unroll
                    for (int u = 0; u < 2; u++) {
                        float4 a = v[u * 8];
#pragma unroll
                        for (int j = 1; j < 8; j++) { a.x += v[u * 8 + j].x; a.y += v[u * 8 + j].y; a.z += v[u * 8 + j].z; a.w += v[u * 8 + j].w; }
                        *(float4*)(cs_s + u * 120 + lane * 4) = a;
                    }
                }
                __syncwarp();
                if (lane == 0) { mbar_arrive(sbase + BAR_AUX); TS(0, 2); }
            }
            if (lane < 27) colsum40(w1 + (size_t)mt * 40 * FF + nt * 216 + lane * 8, FF, &g_cs[mt][3 * DM + nt * 216 + lane * 8]);
            __syncwarp();
            if (lane == 0) { __threadfence(); flag_signal(F->cs[1][nt]); }
#pragma unroll 1
            for (int layer = 0; layer < 2; layer++) {
                {
                    mbar_wait_sleep(sbase + BAR_QDONE, layer);
                    uint32_t seen = 0;
                    poll_flags(lane < 8 ? &F->qkv[layer][head / 6][quarter * 8 + lane] : nullptr, epoch, 0xFFu, seen, lane);
                    if (lane == 0) mbar_arrive(sbase + BAR_Q);
                }
                float km = 0.f;
#pragma unroll 1
                for (int t = 0; t < 16; t++) {
                    mbar_wait_sleep(sbase + BAR_KV + 8 * t, layer);
#pragma unroll
                    for (int u = 0; u < 4; u++) {
                        const int key = lane + u * 32;
                        const uint8_t* kp = smem + OFF_KV + t * 12288 + (key >> 3) * 384 + (key & 7) * 16;
                        const uint4 a = *(const uint4*)kp, b = *(const uint4*)(kp + 128);
                        const uint2 d = *(const uint2*)(kp + 256);
                        uint32_t e = hfma2(a.x, a.x, 0u), f = hfma2(a.y, a.y, 0u);
                        e = hfma2(a.z, a.z, e); f = hfma2(a.w, a.w, f); e = hfma2(b.x, b.x, e); f = hfma2(b.y, b.y, f);
                        e = hfma2(b.z, b.z, e); f = hfma2(b.w, b.w, f); e = hfma2(d.x, d.x, e); f = hfma2(d.y, d.y, f);
                        float n = (bf_lo(e) + bf_hi(e)) + (bf_lo(f) + bf_hi(f));
                        if ((POLY_MASK >> ((key >> 3) & 7)) & 1) n *= 0.25f;
                        km = n >= km ? n : (n != n ? INFINITY : km);
                    }
                }
                const uint32_t kb = __reduce_max_sync(0xffffffffu, __float_as_uint(km));
                if (lane == 0) { *(volatile uint32_t*)(smem + OFF_KMAX + layer * 4) = kb; mbar_arrive(sbase + BAR_KMAX); }
                if (layer == 0) {
                    uint32_t seen = 0;
                    poll_flags(lane == 0 ? F->cs[1][nt] : nullptr, epoch * 16, 1u, seen, lane);
                    load_cs(cs_s + 240, 3 * DM + nt * 216, 216, lane);
                    __syncwarp();
                    if (lane == 0) mbar_arrive(sbase + BAR_AUX);
                }
            }
        } else if (warp_id == 18) {
            Ring rb = {0, 1};
            auto stream = [&](const uint8_t* src, int total, int chunk) {
#pragma unroll 1
                for (int off = 0; off < total; off += chunk) {
                    const int n = total - off < chunk ? total - off : chunk;
                    mbar_wait(sbase + BAR_EMPTYB + 8 * rb.slot, rb.phase);
                    __syncwarp();
                    if (elect_one()) {
                        mbar_expect(sbase + BAR_FULLB + 8 * rb.slot, n);
                        bulk_g2s(sbase + bslot_off(rb.slot), src + off, n, sbase + BAR_FULLB + 8 * rb.slot);
                    }
                    __syncwarp();
                    rb.next<BSLOTS>();
                }
            };
            uint32_t epoch = 0;
#pragma unroll 1
            for (int layer = 0; layer < 2; layer++) {
                if (layer == 1) {
                    flag_wait_warp<500>(F->pack[3], epoch * NHELP); reader_fence();
                    stream(g_wqkv_p + (size_t)nt * 307200, 307200, 30720);
                } else
#pragma unroll 1
                for (int kb = 0; kb < 10; kb++) {
                    mbar_wait(sbase + BAR_EMPTYB + 8 * rb.slot, rb.phase);
                    __syncwarp();
                    if (elect_one()) {
                        mbar_expect(sbase + BAR_FULLB + 8 * rb.slot, 32768);
#pragma unroll
                        for (int b = 0; b < 4; b++) tma_3d(sbase + bslot_off(rb.slot) + b * 8192, &maps.wqkv, (b & 1) * 64, nt * 2 + (b >> 1), kb * 64, sbase + BAR_FULLB + 8 * rb.slot);
                    }
                    __syncwarp();
                    rb.next<BSLOTS>();
                }
                if (layer == 0) epoch = __ldcg(F->epoch) + 1;
#pragma unroll 1
                for (int i = 0; i < 3; i++) {
                    mbar_wait_sleep(sbase + BAR_EMPTYB + 8 * rb.slot, rb.phase);
                    __syncwarp();
                    if (lane == 0) mbar_arrive(sbase + BAR_FULLB + 8 * rb.slot);
                    rb.next<BSLOTS>();
                }
                __syncwarp();
                load_kv(layer, 0, 8, epoch);
                if (lane == 0) TS(2 + layer * 5, 6);
                if (layer == 0) { flag_wait_warp<500>(F->pack[0], epoch * NHELP); reader_fence(); }
                stream(g_wo_p + (size_t)nt * 102400, 102400, 30720);
                if (layer == 0) { flag_wait_warp<500>(F->pack[1], epoch * NHELP); reader_fence(); }
                stream(g_w1_p + (size_t)nt * 276480, 276480, 27648);
                if (layer == 0) { flag_wait_warp<500>(F->pack[2], epoch * NHELP); reader_fence(); }
                stream(g_w2_p + (size_t)nt * 276480, 276480, 30720);
            }
        } else {
            const int r = warp_id - 16, hb = mt * 2 + r;
            const uint32_t ring = sbase + OFF_A + r * A_RING, bfull = sbase + BAR_FULLA + 8 * r * ASLOTS, bempty = sbase + BAR_EMPTYA + 8 * r * ASLOTS;
            Ring ra = {0, 1};
#pragma unroll 1
            for (int kb = 0; kb < 10; kb++) {
                if (kb == ASLOTS - 1 && r == 1) mbar_wait_sleep(sbase + BAR_SCR, 0);
                mbar_wait_sleep(bempty + 8 * ra.slot, ra.phase);
                __syncwarp();
                if (elect_one()) {
                    mbar_expect(bfull + 8 * ra.slot, 8192);
                    tma_2d(ring + ra.slot * 8192, &maps.x, kb * 64, hb * 64, bfull + 8 * ra.slot);
                }
                __syncwarp();
                ra.next<ASLOTS>();
            }
            const uint32_t epoch = __ldcg(F->epoch) + 1;
            auto stream_a = [&](const uint8_t* src, int KB, const uint32_t* flag, uint32_t target, int kid) {
                mbar_wait_sleep(bempty + 8 * ra.slot, ra.phase);
                __syncwarp();
                flag_wait_warp<POLL_NS>(flag, target);
                reader_fence();
                if (lane == 0) TS(kid, 6 + r);
#pragma unroll 1
                for (int kb = 0; kb < KB; kb++) {
                    mbar_wait(bempty + 8 * ra.slot, ra.phase);
                    __syncwarp();
                    if (elect_one()) {
                        mbar_expect(bfull + 8 * ra.slot, 8192);
                        bulk_g2s(ring + ra.slot * 8192, src + kb * 8192, 8192, bfull + 8 * ra.slot);
                    }
                    __syncwarp();
                    ra.next<ASLOTS>();
                }
            };
#pragma unroll 1
            for (int layer = 0; layer < 2; layer++) {
                if (layer == 1) stream_a(g_xb + (size_t)hb * 81920, 10, F->res[1][hb], epoch * 8, 6);
#pragma unroll 1
                for (int i = 0; i < ASLOTS; i++) {
                    mbar_wait_sleep(bempty + 8 * ra.slot, ra.phase);
                    __syncwarp();
                    if (lane == 0) mbar_arrive(bfull + 8 * ra.slot);
                    ra.next<ASLOTS>();
                }
                __syncwarp();
                load_kv(layer, 8 + 4 * r, 4, epoch);
                stream_a(g_o + (size_t)hb * 81920, 10, F->att[layer][hb], epoch * 32, 3 + layer * 5);
                stream_a(g_xa + (size_t)hb * 81920, 10, F->res[layer * 2][hb], epoch * 8, 4 + layer * 5);
                stream_a(g_h + (size_t)hb * 221184, 27, F->w1[layer][hb], epoch * 16, 5 + layer * 5);
            }
            if (w == 0 && r == 0 && lane == 0) *(volatile uint32_t*)F->epoch = epoch;
        }
    } else {
        const int wg = warp_id >> 2, warp = warp_id & 3;
        const int r = wg & 1, h = wg >> 1, hb = mt * 2 + r;
        float* cs_s = (float*)(smem + OFF_CS);
        const uint32_t ring = sbase + OFF_A + r * A_RING;
        {
            float4* scr = (float4*)(smem + OFF_A + 2 * A_RING - 8192);
            if (warp_id < 8) {
                float4 a = make_float4(0.f, 0.f, 0.f, 0.f), b = a;
#pragma unroll
                for (int i = 0; i < 5; i++) {
                    a.x += bf_lo(pre[i].x); a.y += bf_hi(pre[i].x); a.z += bf_lo(pre[i].y); a.w += bf_hi(pre[i].y);
                    b.x += bf_lo(pre[i].z); b.y += bf_hi(pre[i].z); b.z += bf_lo(pre[i].w); b.w += bf_hi(pre[i].w);
                }
                if ((lane & 15) < 15) { float4* d = scr + (warp_id * 2 + (lane >> 4)) * 30 + (lane & 15) * 2; d[0] = a; d[1] = b; }
            } else {
                float sm = 0.f, q = 0.f;
#pragma unroll
                for (int i = 0; i < 5; i++) {
                    const uint32_t u[4] = {pre[i].x, pre[i].y, pre[i].z, pre[i].w};
#pragma unroll
                    for (int j = 0; j < 4; j++) { const float a = bf_lo(u[j]), b = bf_hi(u[j]); sm += a + b; q = fmaf(a, a, q); q = fmaf(b, b, q); }
                }
#pragma unroll
                for (int d = 1; d < 16; d <<= 1) { sm += __shfl_xor_sync(0xffffffffu, sm, d); q += __shfl_xor_sync(0xffffffffu, q, d); }
                if ((lane & 15) == 0) scr[480 + (lane >> 4) * 8 + warp_id - 8] = make_float4(sm, q, 0.f, 0.f);
            }
            asm volatile("fence.proxy.async.shared::cta;" ::: "memory");
            asm volatile("bar.arrive 7, 544;" ::: "memory");
        }
#pragma unroll 1
        for (int layer = 0; layer < 2; layer++) {
            const int kid = 1 + layer * 5;
            {
                float acc[60];
                StatRegs sv; sv.clear();
                { THREAD_IDS;
                gemm_loop<120>(acc, sbase, r, layer * A_PER_LAYER, layer * B_PER_LAYER,
                    layer == 0 ? mkdesc(sbase + h * 16384, 8192, 1024, 1) : mkdesc(sbase + h * 1920, 3840, 128, 0), layer == 0 ? 2048 >> 4 : 7680 >> 4, lane, layer == 0,
                    [&](int kb) {
                        if (kb == 0 && layer == 0) { if (tid == 0) TS(0, 7); }
                        if (kb == (layer == 0 ? 6 : 1)) {
                            if (layer == 0 && tid == 0) TS(1, 6);
                            if (layer == 0) mbar_wait(sbase + BAR_ST, 0);
                            sv.load(&g_stats[layer * 2][hb][0][0], lrow, c);
                        }
                        if (kb == 9) sv.finish();
                    });
                }
                THREAD_IDS;
                if (t128 == 0 && h == 0) TS(kid, 2 + r);
                if (lane == 0) mbar_arrive(sbase + BAR_QDONE);
                const float2 st0 = sv.st0, st1 = sv.st1;
                if (layer == 0) mbar_wait(sbase + BAR_AUX, 0);
                NAMED_BAR(1 + r, 256);
                const float2* cs = (const float2*)(cs_s + h * 120) + c;
                const uint32_t stg = ring + h * 18432;
                const int rg = warp * 2, gh0 = nt * 12 + h * 6;
                const bool poly0 = (POLY_MASK >> rg) & 1, poly1 = (POLY_MASK >> (rg + 1)) & 1;
                uint32_t off[5];
#pragma unroll
                for (int jj = 0; jj < 5; jj++) {
                    const int col = jj * 8 + 2 * c, hl = col >= 20, d = col - hl * 20;
                    off[jj] = stg + hl * 3072 + rg * 384 + (d >> 3) * 128 + g * 16 + (d & 7) * 2;
                }
#pragma unroll
                for (int p = 0; p < 3; p++) {
                    const int which = (gh0 + p * 2) >> 5;
                    const float f0 = which == 0 ? 0.32259642f : (which == 1 && poly0 ? 2.f : 1.f);
                    const float f1 = which == 0 ? 0.32259642f : (which == 1 && poly1 ? 2.f : 1.f);
                    const float a0 = st0.x * f0, b0 = st0.y * f0, a1 = st1.x * f1, b1 = st1.y * f1;
#pragma unroll
                    for (int jj = 0; jj < 5; jj++) {
                        const int j = p * 5 + jj;
                        const float2 cv = cs[j * 4];
                        const uint32_t v0 = pack_bf16(fmaf(acc[4 * j], a0, b0 * cv.x), fmaf(acc[4 * j + 1], a0, b0 * cv.y));
                        const uint32_t v1 = pack_bf16(fmaf(acc[4 * j + 2], a1, b1 * cv.x), fmaf(acc[4 * j + 3], a1, b1 * cv.y));
                        asm volatile("st.shared.b32 [%0], %1;" :: "r"(off[jj] + p * 6144), "r"(v0) : "memory");
                        asm volatile("st.shared.b32 [%0], %1;" :: "r"(off[jj] + p * 6144 + 384), "r"(v1) : "memory");
                    }
                }
#pragma unroll
                for (int i = 0; i < 3; i++) {
                    const int idx = i * 128 + t128, hl = idx >> 6, rr = idx & 63;
                    const int which = (gh0 + hl) >> 5;
                    const bool poly = (POLY_MASK >> (rr >> 3)) & 1;
                    uint32_t w0, w1v;
                    if (which == 0) { w0 = 0x3F803F80u; w1v = 0x00003F80u; }
                    else if (which == 1) { w0 = poly ? 0xC04B4440u : 0u; w1v = poly ? 0x0000BB88u : 0u; }
                    else { w0 = 0x00003F80u; w1v = 0u; }
                    asm volatile("st.shared.v2.b32 [%0], {%1, %2};" :: "r"(stg + hl * 3072 + (rr >> 3) * 384 + 256 + (rr & 7) * 16 + 8), "r"(w0), "r"(w1v) : "memory");
                }
                asm volatile("fence.proxy.async.shared::cta;" ::: "memory");
                NAMED_BAR(3 + wg, 128);
                if (t128 == 0) {
                    if (h == 0) TS(kid, r);
#pragma unroll
                    for (int hl = 0; hl < 6; hl++) bulk_s2g(g_qkvx[layer] + (size_t)(gh0 + hl) * HEAD_BYTES + hb * 3072, stg + hl * 3072, 3072);
                    bulk_commit_wait();
                    flag_signal_bulk(&F->qkv[layer][nt * 2 + h][hb]);
                    release_ring(sbase, r, 8);
                    if (h == 0) TS(kid, 4 + r);
                }
                __syncwarp();
            }
            {
                const uint64_t dK0 = mkdesc(sbase + OFF_KV, 128, 384, 0), dK1 = mkdesc(sbase + OFF_KV + 256, 0, 384, 0), dV = mkdesc(sbase + OFF_KV + 6144, 384, 128, 0);
                const uint32_t* gq0 = (const uint32_t*)(g_qkvx[layer] + (size_t)head * HEAD_BYTES + (quarter * 4 + wg) * 6144 + warp * 768);
                mbar_wait(sbase + BAR_Q, layer);
                uint32_t q0, q1, q2, q3, q4, q5;
                {
                    THREAD_IDS;
                    const uint32_t* gq = gq0 + lane;
                    q0 = __ldcg(gq); q1 = __ldcg(gq + 96); q2 = __ldcg(gq + 32); q3 = __ldcg(gq + 128); q4 = __ldcg(gq + 64); q5 = __ldcg(gq + 160);
                    if (tid == 0) TS(kid + 1, 0);
                }
#pragma unroll 1
                for (int pass = 0; pass < 2; pass++) {
                    const int hbq = (quarter * 4 + wg) * 2 + pass;
                    uint32_t zero = 0, mmask = 0x007F007Fu;
                    asm volatile("" : "+r"(zero), "+r"(mmask));
                    float o[12], s0[32];
                    uint32_t p0[16];
#pragma unroll
                    for (int i = 0; i < 12; i++) o[i] = 0.f;
#pragma unroll
                    for (int i = 0; i < 32; i++) s0[i] = 0.f;
#pragma unroll
                    for (int i = 0; i < 16; i++) p0[i] = 0u;
                    fence_regs(o); fence_regs(s0); fence_regs(p0);
#pragma unroll 1
                    for (int t = 0; t < 16; t++) {
                        const uint32_t cur = t * (12288 >> 4);
                        const uint32_t vprev = t > 0 ? cur - ((12288 - 3072) >> 4) : 0;
                        if (pass == 0) mbar_wait(sbase + BAR_KV + 8 * t, layer);
                        WG_FENCE();
                        ATT_PV(vprev);
                        ATT_QK(cur);
                        WG_COMMIT();
                        WG_WAIT(0);
                        if (pass == 1 && ((0x1148u >> t) & 1)) {
                            THREAD_IDS;
                            if (t == 12) { if (lane < ASLOTS) mbar_arrive(sbase + BAR_EMPTYA + 8 * lane); }
                            else if (lane == 0) mbar_arrive(sbase + BAR_EMPTYB + 8 * (t == 3 ? 2 : (t == 6 ? 3 : 0)));
                        }
                        exp_tile(s0, p0, mmask);
                        WG_FENCE();
                        ATT_PV(cur);
                        ATT_QK(cur + (3072 >> 4));
                        WG_COMMIT();
                        WG_WAIT(0);
                        exp_tile(s0, p0, mmask);
                    }
                    WG_FENCE();
                    ATT_PV((15 * 12288 + 3072) >> 4);
                    WG_COMMIT();
                    THREAD_IDS;
                    const uint32_t* gq = gq0 + lane;
                    const uint32_t q4m = c < 2 ? q4 : 0u, q5m = c < 2 ? q5 : 0u;
                    float n0 = bf_lo(q0) * bf_lo(q0) + bf_hi(q0) * bf_hi(q0) + bf_lo(q2) * bf_lo(q2) + bf_hi(q2) * bf_hi(q2) + bf_lo(q4m) * bf_lo(q4m) + bf_hi(q4m) * bf_hi(q4m);
                    float n1 = bf_lo(q1) * bf_lo(q1) + bf_hi(q1) * bf_hi(q1) + bf_lo(q3) * bf_lo(q3) + bf_hi(q3) * bf_hi(q3) + bf_lo(q5m) * bf_lo(q5m) + bf_hi(q5m) * bf_hi(q5m);
                    if (pass == 0) { q0 = __ldcg(gq + 768); q1 = __ldcg(gq + 768 + 96); q2 = __ldcg(gq + 768 + 32); q3 = __ldcg(gq + 768 + 128); q4 = __ldcg(gq + 768 + 64); q5 = __ldcg(gq + 768 + 160); }
                    n0 += __shfl_xor_sync(0xffffffffu, n0, 1); n0 += __shfl_xor_sync(0xffffffffu, n0, 2);
                    n1 += __shfl_xor_sync(0xffffffffu, n1, 1); n1 += __shfl_xor_sync(0xffffffffu, n1, 2);
                    mbar_wait(sbase + BAR_KMAX, layer);
                    const float kmax = *(volatile float*)(smem + OFF_KMAX + layer * 4) * 1.1f;
                    bool ok = n0 * kmax <= 4096.f && n1 * kmax <= 4096.f;
                    WG_WAIT(0);
                    fence_regs(o);
                    if (pass == 1 && lane < ASLOTS) mbar_arrive(sbase + BAR_EMPTYA + 8 * ASLOTS + 8 * lane);
#pragma unroll
                    for (int i = 0; i < 12; i++) ok = ok && fabsf(o[i]) < 1e30f;
                    if (c == 2) ok = ok && o[8] > 1e-6f && o[10] > 1e-6f;
                    if (!__all_sync(0xffffffffu, ok)) attn_rows_safe(o, gq + pass * 768, g_qkvx[layer], head, lane);
                    const float l0 = __shfl_sync(0xffffffffu, o[8], (lane & ~3) | 2), l1 = __shfl_sync(0xffffffffu, o[10], (lane & ~3) | 2);
                    const float r0 = __fdividef(1.f, l0), r1 = __fdividef(1.f, l1);
                    const int col = head * DH + 2 * c;
                    uint8_t* ob = g_o + (size_t)hbq * 81920 + (col >> 3) * 1024 + lrow * 16 + (col & 7) * 2;
                    *(uint32_t*)ob = pack_bf16(o[0] * r0, o[1] * r0); *(uint32_t*)(ob + 128) = pack_bf16(o[2] * r1, o[3] * r1);
                    *(uint32_t*)(ob + 1024) = pack_bf16(o[4] * r0, o[5] * r0); *(uint32_t*)(ob + 1024 + 128) = pack_bf16(o[6] * r1, o[7] * r1);
                    if (c < 2) { *(uint32_t*)(ob + 2048) = pack_bf16(o[8] * r0, o[9] * r0); *(uint32_t*)(ob + 2048 + 128) = pack_bf16(o[10] * r1, o[11] * r1); }
                    NAMED_BAR(3 + wg, 128);
                    if (t128 == 0) { flag_signal(F->att[layer][hbq]); if (pass == 1) TS(kid + 1, 2 + wg); else if (wg == 0) TS(kid + 1, 1); }
                    __syncwarp();
                }
            }
#pragma unroll 1
            for (int ph = 0; ph < 2; ph++) {
                {
                    uint32_t res[10];
                    float acc[40];
                    { THREAD_IDS;
                    if (layer == 0 && ph == 0) {
                        const uint32_t* r0 = (const uint32_t*)(x + (size_t)(hb * 64 + lrow) * DM + nt * 80 + h * 40) + c;
#pragma unroll
                        for (int j = 0; j < 5; j++) { res[2 * j] = __ldg(r0 + j * 4); res[2 * j + 1] = __ldg(r0 + j * 4 + 8 * DM / 2); }
                    } else {
                        const uint32_t* r0 = (const uint32_t*)((ph == 1 ? g_xa : g_xb) + (size_t)hb * 81920 + nt * 10240 + h * 5120 + lrow * 16) + c;
#pragma unroll
                        for (int j = 0; j < 5; j++) { res[2 * j] = __ldcg(r0 + j * 256); res[2 * j + 1] = __ldcg(r0 + j * 256 + 32); }
                    }
                    res_loop(acc, ph == 0 ? 10 : 27, sbase, r, h, layer * A_PER_LAYER + 16 + ph * 20, layer * B_PER_LAYER + 13 + ph * 14, lane);
                    }
                    THREAD_IDS;
                    if (t128 == 0 && h == 0) TS(kid + 2 + 2 * ph, 2 + r);
                    NAMED_BAR(1 + r, 256);
                    float4* xs = (float4*)(smem + OFF_A + r * A_RING + 20480);
#pragma unroll
                    for (int j = 0; j < 5; j++)
                        xs[(h * 5 + j) * 128 + t128] = h == 0 ? make_float4(acc[20 + 4 * j], acc[21 + 4 * j], acc[22 + 4 * j], acc[23 + 4 * j])
                                                              : make_float4(acc[4 * j], acc[4 * j + 1], acc[4 * j + 2], acc[4 * j + 3]);
                    NAMED_BAR(1 + r, 256);
                    uint32_t ov[10];
                    float s0 = 0.f, s1 = 0.f, q0 = 0.f, q1 = 0.f;
#pragma unroll
                    for (int j = 0; j < 5; j++) {
                        const float4 u = xs[((1 - h) * 5 + j) * 128 + t128];
                        const float m0 = h == 0 ? acc[4 * j] : acc[20 + 4 * j], m1 = h == 0 ? acc[4 * j + 1] : acc[21 + 4 * j];
                        const float m2 = h == 0 ? acc[4 * j + 2] : acc[22 + 4 * j], m3 = h == 0 ? acc[4 * j + 3] : acc[23 + 4 * j];
                        ov[2 * j] = pack_bf16(m0 + u.x + bf_lo(res[2 * j]), m1 + u.y + bf_hi(res[2 * j]));
                        ov[2 * j + 1] = pack_bf16(m2 + u.z + bf_lo(res[2 * j + 1]), m3 + u.w + bf_hi(res[2 * j + 1]));
                        const float a = bf_lo(ov[2 * j]), b = bf_hi(ov[2 * j]), d = bf_lo(ov[2 * j + 1]), e = bf_hi(ov[2 * j + 1]);
                        s0 += a + b; q0 = fmaf(a, a, q0); q0 = fmaf(b, b, q0);
                        s1 += d + e; q1 = fmaf(d, d, q1); q1 = fmaf(e, e, q1);
                    }
                    const bool last = layer == 1 && ph == 1;
                    if (last) stage_tile_swz<5>(ov, ring, h * 5, warp, lane);
                    else {
                        stage_tile<5>(ov, ring + h * 5120, warp, lane);
                        s0 += __shfl_xor_sync(0xffffffffu, s0, 1); q0 += __shfl_xor_sync(0xffffffffu, q0, 1);
                        s1 += __shfl_xor_sync(0xffffffffu, s1, 1); q1 += __shfl_xor_sync(0xffffffffu, q1, 1);
                        s0 += __shfl_xor_sync(0xffffffffu, s0, 2); q0 += __shfl_xor_sync(0xffffffffu, q0, 2);
                        s1 += __shfl_xor_sync(0xffffffffu, s1, 2); q1 += __shfl_xor_sync(0xffffffffu, q1, 2);
                        float2* so = (float2*)(smem + OFF_A + r * A_RING + 16384) + lrow * 2 + h;
                        if (c == 0) { so[0] = make_float2(s0, q0); so[16] = make_float2(s1, q1); }
                    }
                    asm volatile("fence.proxy.async.shared::cta;" ::: "memory");
                    NAMED_BAR(1 + r, 256);
                    if (t128 == 0 && h == 0) {
                        TS(kid + 2 + 2 * ph, r);
                        if (last) {
                            tma_store_3d(&maps.st_out, ring, 0, nt, hb * 64);
                            tma_store_3d(&maps.st_out, ring + 8192, 64, nt, hb * 64);
                        } else {
                            bulk_s2g((ph == 0 ? g_xa : g_xb) + (size_t)hb * 81920 + nt * 10240, ring, 10240);
                            bulk_s2g(&g_stats[layer * 2 + 1 + ph][hb][nt][0], ring + 16384, 1024);
                        }
                        bulk_commit_wait();
                        flag_signal_bulk(F->res[layer * 2 + ph][hb]);
                        release_ring(sbase, r, 16);
                        TS(kid + 2 + 2 * ph, 4 + r);
                    }
                    __syncwarp();
                }
                if (ph == 0) {
                    const float4* stats = &g_stats[layer * 2 + 1][hb][0][0];
                    if (h == 0) w1_phase<112>(sbase, cs_s, r, 0, layer * A_PER_LAYER + 26, layer * B_PER_LAYER + 17, stats, warp);
                    else w1_phase<104>(sbase, cs_s, r, 14, layer * A_PER_LAYER + 26, layer * B_PER_LAYER + 17, stats, warp);
                    asm volatile("fence.proxy.async.shared::cta;" ::: "memory");
                    NAMED_BAR(3 + wg, 128);
                    THREAD_IDS;
                    if (t128 == 0) {
                        if (h == 0) TS(kid + 3, r);
                        bulk_s2g(g_h + (size_t)hb * 221184 + nt * 27648 + h * 14336, ring + h * 14336, h == 0 ? 14336 : 13312);
                        bulk_commit_wait();
                        flag_signal_bulk(F->w1[layer][hb]);
                        release_ring(sbase, r, 8);
                        if (h == 0) TS(kid + 3, 4 + r);
                    }
                    __syncwarp();
                }
            }
        }
    }
}

typedef CUresult (*EncodeFn)(CUtensorMap*, CUtensorMapDataType, cuuint32_t, void*, const cuuint64_t*, const cuuint64_t*, const cuuint32_t*,
                             const cuuint32_t*, CUtensorMapInterleave, CUtensorMapSwizzle, CUtensorMapL2promotion, CUtensorMapFloatOOBfill);
static EncodeFn s_encode;
static CUtensorMap map2d(const void* p, int rows, int cols) {
    CUtensorMap m;
    cuuint64_t dims[2] = {(cuuint64_t)cols, (cuuint64_t)rows}, strides[1] = {(cuuint64_t)cols * 2};
    cuuint32_t box[2] = {64, 64}, es[2] = {1, 1};
    s_encode(&m, CU_TENSOR_MAP_DATA_TYPE_BFLOAT16, 2, (void*)p, dims, strides, box, es, CU_TENSOR_MAP_INTERLEAVE_NONE, CU_TENSOR_MAP_SWIZZLE_128B,
             CU_TENSOR_MAP_L2_PROMOTION_L2_128B, CU_TENSOR_MAP_FLOAT_OOB_FILL_NONE);
    return m;
}
static CUtensorMap map3d(const void* p, int rows, int bn, int nt) {
    CUtensorMap m;
    cuuint64_t dims[3] = {(cuuint64_t)bn, (cuuint64_t)nt, (cuuint64_t)rows}, strides[2] = {(cuuint64_t)bn * 2, (cuuint64_t)bn * nt * 2};
    cuuint32_t box[3] = {64, 1, 64}, es[3] = {1, 1, 1};
    s_encode(&m, CU_TENSOR_MAP_DATA_TYPE_BFLOAT16, 3, (void*)p, dims, strides, box, es, CU_TENSOR_MAP_INTERLEAVE_NONE, CU_TENSOR_MAP_SWIZZLE_128B,
             CU_TENSOR_MAP_L2_PROMOTION_L2_128B, CU_TENSOR_MAP_FLOAT_OOB_FILL_NONE);
    return m;
}

extern "C" void kernel_launch(void* const* d_in, const int* in_sizes, int n_in, void* d_out, int out_size) {
    const bf16* x = (const bf16*)d_in[0];
    const bf16* wqkv = (const bf16*)d_in[1];
    const bf16* wo = (const bf16*)d_in[2];
    const bf16* w1 = (const bf16*)d_in[4];
    const bf16* w2 = (const bf16*)d_in[5];
    if (!s_encode) {
        cudaDriverEntryPointQueryResult qr;
        void* fn = nullptr;
        cudaGetDriverEntryPoint("cuTensorMapEncodeTiled", &fn, cudaEnableDefault, &qr);
        s_encode = (EncodeFn)fn;
        cudaFuncSetAttribute(fused_kernel, cudaFuncAttributeMaxDynamicSharedMemorySize, SMEM_BYTES);
    }
    Maps m;
    m.x = map2d(x, SEQ, DM);
    m.wqkv = map3d(wqkv, DM, 120, 16);
    m.st_out = map3d(d_out, SEQ, 80, 8);
    fused_kernel<<<NHELP + NWORK, NTHREADS, SMEM_BYTES, cudaStreamPerThread>>>(m, x, wqkv, wo, w1, w2);
}
```

```cpp
#include <cuda.h>
#include <cuda_runtime.h>
#include <cuda_bf16.h>
#include <stdint.h>

typedef __nv_bfloat16 bf16;

constexpr int SEQ = 2048, DM = 640, NH = 32, DH = 20, FF = 1728;
constexpr int HEAD_BYTES = 256 * 384;
#define POLY_MASK 0xAD
constexpr int NHELP = 4, NWORK = 128, NTHREADS = 640;

__device__ __align__(1024) uint8_t g_qkvx[2][3 * NH * HEAD_BYTES];
__device__ __align__(1024) uint8_t g_o[SEQ * DM * 2];
__device__ __align__(1024) uint8_t g_xa[SEQ * DM * 2];
__device__ __align__(1024) uint8_t g_xb[SEQ * DM * 2];
__device__ __align__(1024) uint8_t g_h[SEQ * FF * 2];
__device__ __align__(1024) uint8_t g_wo_p[DM * DM * 2];
__device__ __align__(1024) uint8_t g_wqkv_p[DM * 3 * DM * 2];
__device__ __align__(1024) uint8_t g_w1_p[DM * FF * 2];
__device__ __align__(1024) uint8_t g_w2_p[FF * DM * 2];
__device__ __align__(128) float4 g_stats[4][32][8][64];
__device__ __align__(16) float g_cs[4][FF];
struct Flags {
    uint32_t epoch[32];
    uint32_t pack[32][1];
    uint32_t row[32][16];
    uint32_t qkv[16][32];
};
__device__ __align__(128) Flags g_flags;

__device__ __forceinline__ uint32_t smem_u32(const void* p) { return (uint32_t)__cvta_generic_to_shared(p); }
__device__ __forceinline__ void mbar_init(uint32_t bar, int cnt) { asm volatile("mbarrier.init.shared::cta.b64 [%0], %1;" :: "r"(bar), "r"(cnt)); }
__device__ __forceinline__ void mbar_expect(uint32_t bar, uint32_t bytes) { asm volatile("mbarrier.arrive.expect_tx.shared::cta.b64 _, [%0], %1;" :: "r"(bar), "r"(bytes) : "memory"); }
__device__ __forceinline__ void mbar_arrive(uint32_t bar) { asm volatile("mbarrier.arrive.shared::cta.b64 _, [%0];" :: "r"(bar) : "memory"); }
__device__ __forceinline__ void mbar_wait(uint32_t bar, uint32_t parity) {
    asm volatile("{\n.reg .pred p;\n.reg .u32 n;\n"
                 "mbarrier.try_wait.parity.shared::cta.b64 p, [%0], %1;\n@p bra DONE_%=;\nmov.u32 n, 0;\n"
                 "WAIT_%=:\nmbarrier.try_wait.parity.shared::cta.b64 p, [%0], %1;\n@p bra DONE_%=;\n"
                 "add.u32 n, n, 1;\nsetp.lt.u32 p, n, 2097152;\n@p bra WAIT_%=;\ntrap;\nDONE_%=:\n}" :: "r"(bar), "r"(parity) : "memory");
}
__device__ __forceinline__ void mbar_wait_sleep(uint32_t bar, uint32_t parity) {
    asm volatile("{\n.reg .pred p;\n.reg .u32 n;\nmov.u32 n, 0;\n"
                 "WAIT_%=:\nmbarrier.try_wait.parity.shared::cta.b64 p, [%0], %1;\n@p bra DONE_%=;\nnanosleep.u32 100;\n"
                 "add.u32 n, n, 1;\nsetp.lt.u32 p, n, 4194304;\n@p bra WAIT_%=;\ntrap;\nDONE_%=:\n}" :: "r"(bar), "r"(parity) : "memory");
}
__device__ __forceinline__ int fresh_tid() { int t; asm volatile("mov.u32 %0, %%tid.x;" : "=r"(t)); return t; }
#define THREAD_IDS const int tid = fresh_tid(), lane = tid & 31, g = lane >> 2, c = lane & 3, t128 = tid & 127, lrow = warp * 16 + g; (void)g; (void)c; (void)t128; (void)lrow
__device__ __forceinline__ bool elect_one() {
    uint32_t p;
    asm volatile("{\n.reg .pred p;\nelect.sync _|p, 0xffffffff;\nselp.u32 %0, 1, 0, p;\n}" : "=r"(p));
    return p != 0;
}
__device__ __forceinline__ void bulk_g2s(uint32_t dst, const void* src, uint32_t bytes, uint32_t bar) {
    asm volatile("cp.async.bulk.shared::cluster.global.mbarrier::complete_tx::bytes [%0], [%1], %2, [%3];" :: "r"(dst), "l"(src), "r"(bytes), "r"(bar) : "memory");
}
__device__ __forceinline__ void bulk_s2g(void* dst, uint32_t src, uint32_t bytes) {
    asm volatile("cp.async.bulk.global.shared::cta.bulk_group [%0], [%1], %2;" :: "l"(dst), "r"(src), "r"(bytes) : "memory");
}
__device__ __forceinline__ void tma_2d(uint32_t dst, const CUtensorMap* tm, int c0, int c1, uint32_t bar) {
    asm volatile("cp.async.bulk.tensor.2d.shared::cluster.global.mbarrier::complete_tx::bytes [%0], [%1, {%3, %4}], [%2];"
        :: "r"(dst), "l"(tm), "r"(bar), "r"(c0), "r"(c1) : "memory");
}
__device__ __forceinline__ void tma_3d(uint32_t dst, const CUtensorMap* tm, int c0, int c1, int c2, uint32_t bar) {
    asm volatile("cp.async.bulk.tensor.3d.shared::cluster.global.mbarrier::complete_tx::bytes [%0], [%1, {%3, %4, %5}], [%2];"
        :: "r"(dst), "l"(tm), "r"(bar), "r"(c0), "r"(c1), "r"(c2) : "memory");
}
__device__ __forceinline__ void tma_store_3d(const CUtensorMap* tm, uint32_t src, int c0, int c1, int c2) {
    asm volatile("cp.async.bulk.tensor.3d.global.shared::cta.bulk_group [%0, {%2, %3, %4}], [%1];"
        :: "l"(tm), "r"(src), "r"(c0), "r"(c1), "r"(c2) : "memory");
}
__device__ __forceinline__ uint64_t mkdesc(uint32_t addr, uint32_t lbo, uint32_t sbo, uint32_t swz) {
    return (uint64_t)((addr & 0x3FFFF) >> 4) | ((uint64_t)(lbo >> 4) << 16) | ((uint64_t)(sbo >> 4) << 32) | ((uint64_t)swz << 62);
}
#define WG_FENCE() asm volatile("wgmma.fence.sync.aligned;" ::: "memory")
#define WG_COMMIT() asm volatile("wgmma.commit_group.sync.aligned;" ::: "memory")
#define WG_WAIT(n) asm volatile("wgmma.wait_group.sync.aligned %0;" :: "n"(n) : "memory")
#define NAMED_BAR(id, n) asm volatile("bar.sync %0, %1;" :: "r"(id), "n"(n) : "memory")
template<int N> __device__ __forceinline__ void fence_regs(float (&r)[N]) {
#pragma unroll
    for (int i = 0; i < N; i++) asm volatile("" : "+f"(r[i]) :: "memory");
}
template<int N> __device__ __forceinline__ void fence_regs(uint32_t (&r)[N]) {
#pragma unroll
    for (int i = 0; i < N; i++) asm volatile("" : "+r"(r[i]) :: "memory");
}
__device__ __forceinline__ float ex2(float x) { float y; asm("ex2.approx.ftz.f32 %0, %1;" : "=f"(y) : "f"(x)); return y; }
__device__ __forceinline__ float tanh_fast(float x) { float y; asm("tanh.approx.f32 %0, %1;" : "=f"(y) : "f"(x)); return y; }
__device__ __forceinline__ uint32_t pack_bf16(float lo, float hi) { uint32_t r; asm("cvt.rn.bf16x2.f32 %0, %1, %2;" : "=r"(r) : "f"(hi), "f"(lo)); return r; }
__device__ __forceinline__ uint32_t hfma2(uint32_t a, uint32_t b, uint32_t c) { uint32_t r; asm("fma.rn.bf16x2 %0, %1, %2, %3;" : "=r"(r) : "r"(a), "r"(b), "r"(c)); return r; }
__device__ __forceinline__ float bf_lo(uint32_t v) { return __uint_as_float(v << 16); }
__device__ __forceinline__ float bf_hi(uint32_t v) { return __uint_as_float(v & 0xFFFF0000u); }

template<int N> __device__ __forceinline__ void wgmma_ss(float (&d)[N / 2], uint64_t da, uint64_t db, int scale_d);
template<> __device__ __forceinline__ void wgmma_ss<80>(float (&d)[40], uint64_t da, uint64_t db, int scale_d) {
    asm volatile("{\n.reg .pred p;\nsetp.ne.b32 p, %42, 0;\n"
        "wgmma.mma_async.sync.aligned.m64n80k16.f32.bf16.bf16 {%0,%1,%2,%3,%4,%5,%6,%7,%8,%9,%10,%11,%12,%13,%14,%15,%16,%17,%18,%19,%20,%21,%22,%23,%24,%25,%26,%27,%28,%29,%30,%31,%32,%33,%34,%35,%36,%37,%38,%39}, %40, %41, p, 1, 1, 0, 1;\n}"
        : "+f"(d[0]), "+f"(d[1]), "+f"(d[2]), "+f"(d[3]), "+f"(d[4]), "+f"(d[5]), "+f"(d[6]), "+f"(d[7]), "+f"(d[8]), "+f"(d[9]), "+f"(d[10]), "+f"(d[11]), "+f"(d[12]), "+f"(d[13]), "+f"(d[14]), "+f"(d[15]), "+f"(d[16]), "+f"(d[17]), "+f"(d[18]), "+f"(d[19]), "+f"(d[20]), "+f"(d[21]), "+f"(d[22]), "+f"(d[23]), "+f"(d[24]), "+f"(d[25]), "+f"(d[26]), "+f"(d[27]), "+f"(d[28]), "+f"(d[29]), "+f"(d[30]), "+f"(d[31]), "+f"(d[32]), "+f"(d[33]), "+f"(d[34]), "+f"(d[35]), "+f"(d[36]), "+f"(d[37]), "+f"(d[38]), "+f"(d[39])
        : "l"(da), "l"(db), "r"(scale_d));
}
template<> __device__ __forceinline__ void wgmma_ss<104>(float (&d)[52], uint64_t da, uint64_t db, int scale_d) {
    asm volatile("{\n.reg .pred p;\nsetp.ne.b32 p, %54, 0;\n"
        "wgmma.mma_async.sync.aligned.m64n104k16.f32.bf16.bf16 {%0,%1,%2,%3,%4,%5,%6,%7,%8,%9,%10,%11,%12,%13,%14,%15,%16,%17,%18,%19,%20,%21,%22,%23,%24,%25,%26,%27,%28,%29,%30,%31,%32,%33,%34,%35,%36,%37,%38,%39,%40,%41,%42,%43,%44,%45,%46,%47,%48,%49,%50,%51}, %52, %53, p, 1, 1, 0, 1;\n}"
        : "+f"(d[0]), "+f"(d[1]), "+f"(d[2]), "+f"(d[3]), "+f"(d[4]), "+f"(d[5]), "+f"(d[6]), "+f"(d[7]), "+f"(d[8]), "+f"(d[9]), "+f"(d[10]), "+f"(d[11]), "+f"(d[12]), "+f"(d[13]), "+f"(d[14]), "+f"(d[15]), "+f"(d[16]), "+f"(d[17]), "+f"(d[18]), "+f"(d[19]), "+f"(d[20]), "+f"(d[21]), "+f"(d[22]), "+f"(d[23]), "+f"(d[24]), "+f"(d[25]), "+f"(d[26]), "+f"(d[27]), "+f"(d[28]), "+f"(d[29]), "+f"(d[30]), "+f"(d[31]), "+f"(d[32]), "+f"(d[33]), "+f"(d[34]), "+f"(d[35]), "+f"(d[36]), "+f"(d[37]), "+f"(d[38]), "+f"(d[39]), "+f"(d[40]), "+f"(d[41]), "+f"(d[42]), "+f"(d[43]), "+f"(d[44]), "+f"(d[45]), "+f"(d[46]), "+f"(d[47]), "+f"(d[48]), "+f"(d[49]), "+f"(d[50]), "+f"(d[51])
        : "l"(da), "l"(db), "r"(scale_d));
}
template<> __device__ __forceinline__ void wgmma_ss<112>(float (&d)[56], uint64_t da, uint64_t db, int scale_d) {
    asm volatile("{\n.reg .pred p;\nsetp.ne.b32 p, %58, 0;\n"
        "wgmma.mma_async.sync.aligned.m64n112k16.f32.bf16.bf16 {%0,%1,%2,%3,%4,%5,%6,%7,%8,%9,%10,%11,%12,%13,%14,%15,%16,%17,%18,%19,%20,%21,%22,%23,%24,%25,%26,%27,%28,%29,%30,%31,%32,%33,%34,%35,%36,%37,%38,%39,%40,%41,%42,%43,%44,%45,%46,%47,%48,%49,%50,%51,%52,%53,%54,%55}, %56, %57, p, 1, 1, 0, 1;\n}"
        : "+f"(d[0]), "+f"(d[1]), "+f"(d[2]), "+f"(d[3]), "+f"(d[4]), "+f"(d[5]), "+f"(d[6]), "+f"(d[7]), "+f"(d[8]), "+f"(d[9]), "+f"(d[10]), "+f"(d[11]), "+f"(d[12]), "+f"(d[13]), "+f"(d[14]), "+f"(d[15]), "+f"(d[16]), "+f"(d[17]), "+f"(d[18]), "+f"(d[19]), "+f"(d[20]), "+f"(d[21]), "+f"(d[22]), "+f"(d[23]), "+f"(d[24]), "+f"(d[25]), "+f"(d[26]), "+f"(d[27]), "+f"(d[28]), "+f"(d[29]), "+f"(d[30]), "+f"(d[31]), "+f"(d[32]), "+f"(d[33]), "+f"(d[34]), "+f"(d[35]), "+f"(d[36]), "+f"(d[37]), "+f"(d[38]), "+f"(d[39]), "+f"(d[40]), "+f"(d[41]), "+f"(d[42]), "+f"(d[43]), "+f"(d[44]), "+f"(d[45]), "+f"(d[46]), "+f"(d[47]), "+f"(d[48]), "+f"(d[49]), "+f"(d[50]), "+f"(d[51]), "+f"(d[52]), "+f"(d[53]), "+f"(d[54]), "+f"(d[55])
        : "l"(da), "l"(db), "r"(scale_d));
}
template<> __device__ __forceinline__ void wgmma_ss<120>(float (&d)[60], uint64_t da, uint64_t db, int scale_d) {
    asm volatile("{\n.reg .pred p;\nsetp.ne.b32 p, %62, 0;\n"
        "wgmma.mma_async.sync.aligned.m64n120k16.f32.bf16.bf16 {%0,%1,%2,%3,%4,%5,%6,%7,%8,%9,%10,%11,%12,%13,%14,%15,%16,%17,%18,%19,%20,%21,%22,%23,%24,%25,%26,%27,%28,%29,%30,%31,%32,%33,%34,%35,%36,%37,%38,%39,%40,%41,%42,%43,%44,%45,%46,%47,%48,%49,%50,%51,%52,%53,%54,%55,%56,%57,%58,%59}, %60, %61, p, 1, 1, 0, 1;\n}"
        : "+f"(d[0]), "+f"(d[1]), "+f"(d[2]), "+f"(d[3]), "+f"(d[4]), "+f"(d[5]), "+f"(d[6]), "+f"(d[7]), "+f"(d[8]), "+f"(d[9]), "+f"(d[10]), "+f"(d[11]), "+f"(d[12]), "+f"(d[13]), "+f"(d[14]), "+f"(d[15]), "+f"(d[16]), "+f"(d[17]), "+f"(d[18]), "+f"(d[19]), "+f"(d[20]), "+f"(d[21]), "+f"(d[22]), "+f"(d[23]), "+f"(d[24]), "+f"(d[25]), "+f"(d[26]), "+f"(d[27]), "+f"(d[28]), "+f"(d[29]), "+f"(d[30]), "+f"(d[31]), "+f"(d[32]), "+f"(d[33]), "+f"(d[34]), "+f"(d[35]), "+f"(d[36]), "+f"(d[37]), "+f"(d[38]), "+f"(d[39]), "+f"(d[40]), "+f"(d[41]), "+f"(d[42]), "+f"(d[43]), "+f"(d[44]), "+f"(d[45]), "+f"(d[46]), "+f"(d[47]), "+f"(d[48]), "+f"(d[49]), "+f"(d[50]), "+f"(d[51]), "+f"(d[52]), "+f"(d[53]), "+f"(d[54]), "+f"(d[55]), "+f"(d[56]), "+f"(d[57]), "+f"(d[58]), "+f"(d[59])
        : "l"(da), "l"(db), "r"(scale_d));
}
template<int SCALE_D> __device__ __forceinline__ void wgmma_qk(float (&d)[32], uint32_t a0, uint32_t a1, uint32_t a2, uint32_t a3, uint64_t db) {
    asm volatile("wgmma.mma_async.sync.aligned.m64n64k16.f32.bf16.bf16 {%0,%1,%2,%3,%4,%5,%6,%7,%8,%9,%10,%11,%12,%13,%14,%15,%16,%17,%18,%19,%20,%21,%22,%23,%24,%25,%26,%27,%28,%29,%30,%31}, {%32,%33,%34,%35}, %36, %37, 1, 1, 0;"
        : "+f"(d[0]), "+f"(d[1]), "+f"(d[2]), "+f"(d[3]), "+f"(d[4]), "+f"(d[5]), "+f"(d[6]), "+f"(d[7]), "+f"(d[8]), "+f"(d[9]), "+f"(d[10]), "+f"(d[11]), "+f"(d[12]), "+f"(d[13]), "+f"(d[14]), "+f"(d[15]), "+f"(d[16]), "+f"(d[17]), "+f"(d[18]), "+f"(d[19]), "+f"(d[20]), "+f"(d[21]), "+f"(d[22]), "+f"(d[23]), "+f"(d[24]), "+f"(d[25]), "+f"(d[26]), "+f"(d[27]), "+f"(d[28]), "+f"(d[29]), "+f"(d[30]), "+f"(d[31])
        : "r"(a0), "r"(a1), "r"(a2), "r"(a3), "l"(db), "n"(SCALE_D));
}
template<int SCALE_D> __device__ __forceinline__ void wgmma_pv(float (&d)[12], uint32_t a0, uint32_t a1, uint32_t a2, uint32_t a3, uint64_t db) {
    asm volatile("wgmma.mma_async.sync.aligned.m64n24k16.f32.bf16.bf16 {%0,%1,%2,%3,%4,%5,%6,%7,%8,%9,%10,%11}, {%12,%13,%14,%15}, %16, %17, 1, 1, 1;"
        : "+f"(d[0]), "+f"(d[1]), "+f"(d[2]), "+f"(d[3]), "+f"(d[4]), "+f"(d[5]), "+f"(d[6]), "+f"(d[7]), "+f"(d[8]), "+f"(d[9]), "+f"(d[10]), "+f"(d[11])
        : "r"(a0), "r"(a1), "r"(a2), "r"(a3), "l"(db), "n"(SCALE_D));
}

__device__ __forceinline__ void mbar_arrive_n(uint32_t bar, uint32_t n) { asm volatile("mbarrier.arrive.shared::cta.b64 _, [%0], %1;" :: "r"(bar), "r"(n) : "memory"); }
__device__ __forceinline__ uint32_t ld_acquire(const uint32_t* p) { uint32_t v; asm volatile("ld.acquire.gpu.global.u32 %0, [%1];" : "=r"(v) : "l"(p) : "memory"); return v; }
__device__ __forceinline__ void flag_signal(uint32_t* p) { asm volatile("red.release.gpu.global.add.u32 [%0], 1;" :: "l"(p) : "memory"); }
template<int SLEEP>
__device__ __forceinline__ void flag_wait_warp(const uint32_t* p, uint32_t target) {
    int spins = 0;
    while (__any_sync(0xffffffffu, (int)(ld_acquire(p) - target) < 0)) { if (SLEEP) __nanosleep(SLEEP); if (++spins > (1 << 21)) __trap(); }
}
__device__ __forceinline__ void bulk_commit_wait() {
    asm volatile("cp.async.bulk.commit_group;" ::: "memory");
    asm volatile("cp.async.bulk.wait_group 0;" ::: "memory");
}

constexpr int ASLOTS = 6, BSLOTS = 4;
constexpr uint32_t B_SLOT = 32768, OFF_A = BSLOTS * B_SLOT, A_RING = ASLOTS * 8192, OFF_KV = B_SLOT, OFF_CS = OFF_A + 2 * A_RING;
constexpr uint32_t OFF_ST0 = OFF_CS + 960, OFF_ONES = OFF_ST0 + 1024, OFF_BAR = OFF_ONES + 128;
constexpr uint32_t BAR_FULLA = OFF_BAR, BAR_EMPTYA = BAR_FULLA + 8 * 2 * ASLOTS, BAR_FULLB = BAR_EMPTYA + 8 * 2 * ASLOTS, BAR_EMPTYB = BAR_FULLB + 8 * BSLOTS;
constexpr uint32_t BAR_KV = BAR_EMPTYB + 8 * BSLOTS, BAR_KMAX = BAR_KV + 8 * 16, BAR_Q = BAR_KMAX + 8, BAR_AUX = BAR_Q + 40, BAR_WQ = BAR_AUX + 8, BAR_DUMMY = BAR_WQ + 8, OFF_KMAX = BAR_DUMMY + 8, SMEM_BYTES = OFF_KMAX + 16;
__device__ __forceinline__ uint32_t bslot_off(uint32_t s) { return ((s + 3) & 3) * B_SLOT; }

struct Ring {
    uint32_t slot, phase;
    template<int N> __device__ __forceinline__ void next() { if (++slot == N) { slot = 0; phase ^= 1; } }
    template<int N> __device__ __forceinline__ void set(int idx) { slot = idx % N; phase = (idx / N) & 1; }
};
constexpr int A_PER_LAYER = 71, B_PER_LAYER = 36;
__device__ __forceinline__ uint64_t desc_add(uint64_t d, uint32_t off) {
    uint32_t lo = (uint32_t)d + off, hi = (uint32_t)(d >> 32);
    uint64_t r; asm("mov.b64 %0, {%1, %2};" : "=l"(r) : "r"(lo), "r"(hi)); return r;
}

struct Maps { CUtensorMap x, wqkv, wq_rows, st_out; };

__device__ __forceinline__ void wo_loop(float (&acc)[40], uint32_t sbase, int r, int h, int a0, int b0, int lane) {
    const uint64_t adesc = mkdesc(sbase + OFF_A + r * A_RING, 1024, 128, 0), bdesc = mkdesc(sbase, 1280, 128, 0);
#pragma unroll
    for (int i = 0; i < 40; i++) acc[i] = 0.f;
    fence_regs(acc);
    Ring ra, rb;
    ra.set<ASLOTS>(a0 + h); rb.set<BSLOTS>(b0);
#pragma unroll
    for (int i = 0; i < BSLOTS; i++) { mbar_wait(sbase + BAR_FULLB + 8 * rb.slot, rb.phase); rb.next<BSLOTS>(); }
    const uint32_t abase = sbase + BAR_FULLA + 8 * r * ASLOTS;
    uint32_t as8 = ra.slot * 8, aph = ra.phase;
#pragma unroll
    for (int i = 0; i < 5; i++) {
        const uint32_t ob = h == 0 ? (((2 * i) / 3) * B_SLOT + ((2 * i) % 3) * 10240) >> 4 : (((2 * i + 1) / 3) * B_SLOT + ((2 * i + 1) % 3) * 10240) >> 4;
        mbar_wait(abase + as8, aph);
        WG_FENCE();
#pragma unroll
        for (int k = 0; k < 4; k++) wgmma_ss<80>(acc, desc_add(adesc, as8 * 64 + k * 128), desc_add(bdesc, ob + k * (2560 >> 4)), 1);
        WG_COMMIT();
        if (i < 2) {
            WG_WAIT(0);
            if (lane == 0) {
                mbar_arrive_n(abase + as8 + (BAR_EMPTYA - BAR_FULLA), 4);
                if (i == 1) mbar_arrive(sbase + BAR_EMPTYB + 8);
            }
        }
        as8 += 16;
        if (as8 >= 8 * ASLOTS) { as8 -= 8 * ASLOTS; aph ^= 1; }
    }
    WG_WAIT(0);
    fence_regs(acc);
    if (lane < BSLOTS && lane != 1) mbar_arrive(sbase + BAR_EMPTYB + 8 * lane);
}
template<int NW, int KPB, bool RAW, typename Hook>
__device__ __forceinline__ void seg_loop(float (&acc)[NW / 2], float (&csum)[4], int k0, int k1, uint32_t sbase, int r, int a0, int b0, uint64_t bdesc,
                                         int release_k, int shared_lo, int shared_hi, uint32_t cnt_first, uint32_t cnt_last, int wait_bar, int pass_bar, int pass_k, int lane, Hook hook) {
    constexpr uint32_t bstep = RAW ? 2048 >> 4 : (2 * NW * 16) >> 4, bblock = RAW ? 16384 >> 4 : 4 * bstep, astep = RAW ? 2 : 128;
    const uint64_t adesc = RAW ? mkdesc(sbase + OFF_A + r * A_RING, 16, 1024, 1) : mkdesc(sbase + OFF_A + r * A_RING, 1024, 128, 0);
#pragma unroll
    for (int i = 0; i < NW / 2; i++) acc[i] = 0.f;
    fence_regs(acc);
    Ring ra, rb;
    ra.set<ASLOTS>(a0); rb.set<BSLOTS>(b0);
    const uint32_t abase = sbase + BAR_FULLA + 8 * r * ASLOTS, dummy = sbase + BAR_DUMMY;
    uint32_t as8 = ra.slot * 8, aph = ra.phase, prev_a = dummy, prev_b = dummy, cnt = 4, cnta = 4;
    const bool lead = lane == 0;
    if (wait_bar) NAMED_BAR(wait_bar, 256);
#pragma unroll 1
    for (int kb = 0; kb < k1; kb += KPB) {
        mbar_wait(sbase + BAR_FULLB + 8 * rb.slot, rb.phase);
        const uint32_t ob = bslot_off(rb.slot) >> 4;
#pragma unroll
        for (int j = 0; j < KPB; j++) {
            if (kb + j >= k0 && kb + j < k1) {
                mbar_wait(abase + as8, aph);
                WG_FENCE();
#pragma unroll
                for (int k = 0; k < 4; k++) wgmma_ss<NW>(acc, desc_add(adesc, as8 * 64 + k * astep), desc_add(bdesc, ob + j * bblock + k * bstep), 1);
                if (RAW) {
#pragma unroll
                    for (int k = 0; k < 4; k++)
                        asm volatile("wgmma.mma_async.sync.aligned.m64n8k16.f32.bf16.bf16 {%0,%1,%2,%3}, %4, %5, 1, 1, 1, 1, 0;"
                            : "+f"(csum[0]), "+f"(csum[1]), "+f"(csum[2]), "+f"(csum[3])
                            : "l"(desc_add(bdesc, ob + j * bblock + r * (8192 >> 4) + k * bstep)), "l"(mkdesc(sbase + OFF_ONES, 0, 0, 0)));
                }
                WG_COMMIT();
                if (RAW) hook(as8);
                if (kb + j == pass_k) asm volatile("bar.arrive %0, 256;" :: "r"(pass_bar) : "memory");
                const uint32_t rel = prev_a, reln = cnta;
                cnta = kb + j >= shared_lo && kb + j < shared_hi ? 2 : 4;
                prev_a = kb + j < release_k ? abase + as8 + (BAR_EMPTYA - BAR_FULLA) : dummy;
                as8 += 8;
                if (as8 == 8 * ASLOTS) { as8 = 0; aph ^= 1; }
                WG_WAIT(1);
                if (lead) {
                    mbar_arrive_n(rel, reln);
                    if (j == 0) mbar_arrive_n(prev_b, cnt);
                }
            }
        }
        if (!RAW) hook(kb);
        prev_b = sbase + BAR_EMPTYB + 8 * rb.slot;
        cnt = kb == 0 ? cnt_first : 2;
        rb.next<BSLOTS>();
    }
    WG_WAIT(0);
    fence_regs(acc);
    if (RAW) fence_regs(csum);
    if (lead) { mbar_arrive_n(prev_a, cnta); mbar_arrive_n(prev_b, cnt_last); }
}
__device__ __forceinline__ void release_ring(uint32_t sbase, int r, uint32_t cnt) {
#pragma unroll
    for (int s = 0; s < ASLOTS; s++) mbar_arrive_n(sbase + BAR_EMPTYA + 8 * (r * ASLOTS + s), cnt);
}
struct StatRegs {
    float4 v[4];
    float2 st0, st1;
    __device__ __forceinline__ void clear() { v[0] = v[1] = v[2] = v[3] = make_float4(0.f, 0.f, 0.f, 0.f); st0 = st1 = make_float2(0.f, 0.f); }
    __device__ __forceinline__ void load(const float4* p  , int lrow, int c) {
        v[0] = __ldcg(p + c * 64 + lrow); v[1] = __ldcg(p + (c + 4) * 64 + lrow);
        v[2] = __ldcg(p + c * 64 + lrow + 8); v[3] = __ldcg(p + (c + 4) * 64 + lrow + 8);
    }
    static __device__ __forceinline__ float2 fin(const float4 a, const float4 b) {
        float s = (a.x + a.z) + (b.x + b.z), q = (a.y + a.w) + (b.y + b.w);
        s += __shfl_xor_sync(0xffffffffu, s, 1); q += __shfl_xor_sync(0xffffffffu, q, 1);
        s += __shfl_xor_sync(0xffffffffu, s, 2); q += __shfl_xor_sync(0xffffffffu, q, 2);
        const float mean = s * (1.f / DM);
        const float rstd = rsqrtf(fmaxf(q * (1.f / DM) - mean * mean, 0.f) + 1e-5f);
        return make_float2(rstd, -mean * rstd);
    }
    __device__ __forceinline__ void finish() { st0 = fin(v[0], v[1]); st1 = fin(v[2], v[3]); }
};
template<int NB>
__device__ __forceinline__ void stage_tile_swz(const uint32_t (&ov)[2 * NB], uint32_t stg, int blk0, int warp, int lane) {
    const int srow = warp * 16 + (lane & 15);
#pragma unroll
    for (int j = 0; j < NB; j += 2) {
        const int blk = blk0 + j + (j + 1 < NB ? (lane >> 4) : 0);
        const uint32_t addr = stg + (blk >> 3) * 8192 + srow * 128 + (((blk & 7) ^ (srow & 7)) << 4);
        if (j + 1 < NB)
            asm volatile("stmatrix.sync.aligned.m8n8.x4.shared.b16 [%0], {%1, %2, %3, %4};"
                :: "r"(addr), "r"(ov[2 * j]), "r"(ov[2 * j + 1]), "r"(ov[(2 * j + 2) % (2 * NB)]), "r"(ov[(2 * j + 3) % (2 * NB)]) : "memory");
        else
            asm volatile("stmatrix.sync.aligned.m8n8.x2.shared.b16 [%0], {%1, %2};" :: "r"(addr), "r"(ov[2 * j]), "r"(ov[2 * j + 1]) : "memory");
    }
}
template<int NW>
__device__ __forceinline__ void w1_phase(uint32_t sbase, const float* cs_s, int r, int blk0, int a0, int b0, const float4* stats, int warp, uint8_t* dst) {
    float acc[NW / 2];
    StatRegs sv; sv.clear();
    { THREAD_IDS;
    float nocs[4];
    seg_loop<NW, 2, false>(acc, nocs, 0, 10, sbase, r, a0, b0, mkdesc(sbase, NW * 16, 128, 0), 10, blk0 ? 0 : 4, blk0 ? 6 : 10, 2, 2, blk0 ? 9 + r : 0, (blk0 ? 11 : 9) + r, blk0 ? 9 : 8, lane,
        [&](int kb) { if (kb == 0) sv.load(stats, lrow, c); if (kb == 6) sv.finish(); });
    }
    THREAD_IDS;
    float2 st0 = sv.st0, st1 = sv.st1;
    st0.x *= 0.5f; st0.y *= 0.5f; st1.x *= 0.5f; st1.y *= 0.5f;
    mbar_wait(sbase + BAR_AUX, 0);
    const float2* cs = (const float2*)(cs_s + 240 + blk0 * 8) + c;
    uint32_t* out = (uint32_t*)(dst + lrow * 16) + c;
#pragma unroll
    for (int j = 0; j < NW / 8; j++) {
        const float2 cv = cs[j * 4];
        const float h0 = fmaf(acc[4 * j], st0.x, st0.y * cv.x), h1 = fmaf(acc[4 * j + 1], st0.x, st0.y * cv.y);
        const float h2 = fmaf(acc[4 * j + 2], st1.x, st1.y * cv.x), h3 = fmaf(acc[4 * j + 3], st1.x, st1.y * cv.y);
        out[j * 256] = pack_bf16(fmaf(h0, tanh_fast(h0), h0), fmaf(h1, tanh_fast(h1), h1));
        out[j * 256 + 32] = pack_bf16(fmaf(h2, tanh_fast(h2), h2), fmaf(h3, tanh_fast(h3), h3));
    }
}

__device__ __forceinline__ uint32_t poly_pair(float y0, float y1, uint32_t mmask) {
    const uint32_t L = __byte_perm(__float_as_uint(y0), __float_as_uint(y1), 0x6521);
    uint32_t U, Y;
    asm("lop3.b32 %0, %1, %2, 0x3F003F00, 0xEA;" : "=r"(U) : "r"(L), "r"(mmask));
    asm("lop3.b32 %0, %1, %2, 0x00010001, 0xBA;" : "=r"(Y) : "r"(L), "r"(mmask));
    return hfma2(L, U, Y);
}
__device__ __forceinline__ void exp_tile(float (&s)[32], uint32_t (&p)[16], uint32_t mmask) {
    fence_regs(s);
#pragma unroll
    for (int b = 0; b < 8; b++) {
        if ((POLY_MASK >> b) & 1) {
            p[2 * b] = poly_pair(s[4 * b], s[4 * b + 1], mmask);
            p[2 * b + 1] = poly_pair(s[4 * b + 2], s[4 * b + 3], mmask);
        } else {
            p[2 * b] = pack_bf16(ex2(s[4 * b]), ex2(s[4 * b + 1]));
            p[2 * b + 1] = pack_bf16(ex2(s[4 * b + 2]), ex2(s[4 * b + 3]));
        }
    }
    fence_regs(p);
}
__device__ __forceinline__ void mma16816(float (&d)[4], uint32_t a0, uint32_t a1, uint32_t a2, uint32_t a3, uint32_t b0, uint32_t b1) {
    asm volatile("mma.sync.aligned.m16n8k16.row.col.f32.bf16.bf16.f32 {%0,%1,%2,%3}, {%4,%5,%6,%7}, {%8,%9}, {%0,%1,%2,%3};"
        : "+f"(d[0]), "+f"(d[1]), "+f"(d[2]), "+f"(d[3]) : "r"(a0), "r"(a1), "r"(a2), "r"(a3), "r"(b0), "r"(b1));
}
__device__ __forceinline__ uint32_t movtrans(uint32_t v) { uint32_t r; asm volatile("movmatrix.sync.aligned.m8n8.trans.b16 %0, %1;" : "=r"(r) : "r"(v)); return r; }
__device__ __forceinline__ void attn_rows_safe(float (&o)[12], const uint32_t* gq, const uint8_t* qkvx, int head, int lane) {
    const int c = lane & 3;
    const uint32_t q0 = __ldcg(gq), q1 = __ldcg(gq + 96), q2 = __ldcg(gq + 32), q3 = __ldcg(gq + 128);
    const uint32_t q4 = c < 2 ? __ldcg(gq + 64) : 0u, q5 = c < 2 ? __ldcg(gq + 160) : 0u;
    const uint32_t* gk = (const uint32_t*)(qkvx + (size_t)(NH + head) * HEAD_BYTES) + lane;
    const uint32_t* gv = (const uint32_t*)(qkvx + (size_t)(2 * NH + head) * HEAD_BYTES) + lane;
    float oo[3][4];
#pragma unroll
    for (int j = 0; j < 3; j++) { oo[j][0] = oo[j][1] = oo[j][2] = oo[j][3] = 0.f; }
    float m0 = -INFINITY, m1 = -INFINITY;
#pragma unroll 1
    for (int t = 0; t < SEQ / 16; t++) {
        float s[2][4];
#pragma unroll
        for (int b = 0; b < 2; b++) {
            const uint32_t* kp = gk + (t * 2 + b) * 96;
            const uint32_t k0 = __ldcg(kp), k1 = __ldcg(kp + 32), k2 = __ldcg(kp + 64);
            s[b][0] = s[b][1] = s[b][2] = s[b][3] = 0.f;
            mma16816(s[b], q0, q1, q2, q3, k0, k1);
            mma16816(s[b], q4, q5, 0u, 0u, k2, 0u);
            const float f = (POLY_MASK >> ((t * 2 + b) & 7)) & 1 ? 0.5f : 1.f;
            s[b][0] *= f; s[b][1] *= f; s[b][2] *= f; s[b][3] *= f;
        }
        float n0 = fmaxf(fmaxf(m0, fmaxf(s[0][0], s[0][1])), fmaxf(s[1][0], s[1][1]));
        float n1 = fmaxf(fmaxf(m1, fmaxf(s[0][2], s[0][3])), fmaxf(s[1][2], s[1][3]));
        n0 = fmaxf(n0, __shfl_xor_sync(0xffffffffu, n0, 1)); n0 = fmaxf(n0, __shfl_xor_sync(0xffffffffu, n0, 2));
        n1 = fmaxf(n1, __shfl_xor_sync(0xffffffffu, n1, 1)); n1 = fmaxf(n1, __shfl_xor_sync(0xffffffffu, n1, 2));
        const float a0 = ex2(m0 - n0), a1 = ex2(m1 - n1);
        m0 = n0; m1 = n1;
        const uint32_t p0 = pack_bf16(ex2(s[0][0] - m0), ex2(s[0][1] - m0)), p1 = pack_bf16(ex2(s[0][2] - m1), ex2(s[0][3] - m1));
        const uint32_t p2 = pack_bf16(ex2(s[1][0] - m0), ex2(s[1][1] - m0)), p3 = pack_bf16(ex2(s[1][2] - m1), ex2(s[1][3] - m1));
#pragma unroll
        for (int j = 0; j < 3; j++) {
            const uint32_t v0 = movtrans(__ldcg(gv + (t * 2) * 96 + j * 32)), v1 = movtrans(__ldcg(gv + (t * 2 + 1) * 96 + j * 32));
            oo[j][0] *= a0; oo[j][1] *= a0; oo[j][2] *= a1; oo[j][3] *= a1;
            mma16816(oo[j], p0, p1, p2, p3, v0, v1);
        }
    }
#pragma unroll
    for (int j = 0; j < 3; j++) { o[4 * j] = oo[j][0]; o[4 * j + 1] = oo[j][1]; o[4 * j + 2] = oo[j][2]; o[4 * j + 3] = oo[j][3]; }
}
#define ATT_QK(off) do { wgmma_qk<0>(s0, q0, q1, q2, q3, desc_add(dK0, (off))); wgmma_qk<1>(s0, q4, q5, zero, zero, desc_add(dK1, (off))); } while (0)
#define ATT_PV(off) do { _Pragma("unroll") for (int j = 0; j < 4; j++) wgmma_pv<1>(o, p0[4 * j], p0[4 * j + 1], p0[4 * j + 2], p0[4 * j + 3], desc_add(dV, (off) + ((j * 768) >> 4))); } while (0)

constexpr int PK_STAGES = 4, PK_SLOT = 30720, PK_OUT = PK_STAGES * PK_SLOT, PK_BAR = PK_OUT + 3 * PK_SLOT;
template<int BN, int K, int R, int MODE>
__device__ __forceinline__ void pack_weight(const bf16* __restrict__ w, uint8_t* __restrict__ dst, uint8_t* smem, uint32_t sbase, int& seq, int tid, uint32_t* prev_flag) {
    constexpr int NG = BN / 8, N8 = 8 * NG, P = N8 * 16, NST = K / R / NHELP;
    static_assert(R * P <= PK_SLOT && (K / R) % NHELP == 0, "");
    const uint32_t bars = sbase + PK_BAR;
    auto issue = [&](int i) {
        const int sl = (seq + i) % PK_STAGES;
        mbar_expect(bars + 8 * sl, R * P);
        if (MODE == 2) {
#pragma unroll
            for (int j = 0; j < R / 8; j++) {
                const int d = (i * NHELP + blockIdx.x) * (R / 8) + j, src = d < 112 ? (d / 14) * 27 + d % 14 : ((d - 112) / 13) * 27 + 14 + (d - 112) % 13;
                bulk_g2s(sbase + sl * PK_SLOT + j * 8 * P, (const char*)w + (size_t)src * 8 * P, 8 * P, bars + 8 * sl);
            }
        } else bulk_g2s(sbase + sl * PK_SLOT, (const char*)w + (size_t)(i * NHELP + blockIdx.x) * R * P, R * P, bars + 8 * sl);
    };
    const bool storer = (tid & 31) == 0 && tid < (MODE == 1 ? 512 : 256);
    if (tid == 512) for (int i = 0; i < PK_STAGES && i < NST; i++) issue(i);
    constexpr int NE = (R * N8 + NTHREADS - 1) / NTHREADS;
    int so[NE], dofs[NE];
#pragma unroll
    for (int j = 0; j < NE; j++) {
        const int e = tid + j * NTHREADS;
        const int kr = e & 7, u = e >> 3, kg = u / N8, v = u % N8, n8 = (v & ~7) | ((v + kr) & 7), nt = n8 / NG, ng = n8 % NG;
        so[j] = e < R * N8 ? (kg * 8 + kr) * P + n8 * 16 : -1;
        dofs[j] = ((nt * (R / 8) + kg) * NG + ng) * 128 + kr * 16;
    }
    float cs[8] = {0.f, 0.f, 0.f, 0.f, 0.f, 0.f, 0.f, 0.f};
#pragma unroll 1
    for (int i = 0; i < NST; i++) {
        const int sl = (seq + i) % PK_STAGES, ob = PK_OUT + ((seq + i) % 3) * PK_SLOT;
        mbar_wait(bars + 8 * sl, ((seq + i) / PK_STAGES) & 1);
        if (BN == 216 && tid < N8) {
#pragma unroll
            for (int kr = 0; kr < R; kr++) {
                const uint4 u = *(const uint4*)(smem + sl * PK_SLOT + kr * P + tid * 16);
                cs[0] += bf_lo(u.x); cs[1] += bf_hi(u.x); cs[2] += bf_lo(u.y); cs[3] += bf_hi(u.y);
                cs[4] += bf_lo(u.z); cs[5] += bf_hi(u.z); cs[6] += bf_lo(u.w); cs[7] += bf_hi(u.w);
            }
        }
        uint4 v[NE];
#pragma unroll
        for (int j = 0; j < NE; j++) if (so[j] >= 0) v[j] = *(const uint4*)(smem + sl * PK_SLOT + so[j]);
#pragma unroll
        for (int j = 0; j < NE; j++) if (so[j] >= 0) *(uint4*)(smem + ob + dofs[j]) = v[j];
        asm volatile("fence.proxy.async.shared::cta;" ::: "memory");
        if (storer) asm volatile("cp.async.bulk.wait_group.read 1;" ::: "memory");
        else if (i == 0 && (tid & 31) == 0) asm volatile("cp.async.bulk.wait_group.read 0;" ::: "memory");
        if (i == 2 && (tid & 31) == 0) {
            if (storer) asm volatile("cp.async.bulk.wait_group 2;" ::: "memory"); else asm volatile("cp.async.bulk.wait_group 0;" ::: "memory");
            __threadfence();
        }
        __syncthreads();
        if (i == 2 && tid == 608 && prev_flag) flag_signal(prev_flag);
        if (tid == 512 && i + PK_STAGES < NST) issue(i + PK_STAGES);
        if (storer) {
            const int kg0 = (i * NHELP + blockIdx.x) * (R / 8), nt = (tid >> 5) & 7;
            if (MODE == 1) {
                constexpr int G0 = (NG + 1) / 2 * 128, G1 = NG / 2 * 128;
                if (tid < 256) bulk_s2g(dst + (size_t)nt * (K / 8) * NG * 128 + kg0 * G0, sbase + ob + nt * NG * 128, G0);
                else bulk_s2g(dst + (size_t)nt * (K / 8) * NG * 128 + (K / 8) * G0 + kg0 * G1, sbase + ob + nt * NG * 128 + G0, G1);
            } else bulk_s2g(dst + ((size_t)nt * (K / 8) + kg0) * NG * 128, sbase + ob + nt * (R / 8) * NG * 128, (R / 8) * NG * 128);
            asm volatile("cp.async.bulk.commit_group;" ::: "memory");
        }
    }
    seq += NST;
    if (BN == 216 && tid < N8) {
        *(float4*)&g_cs[blockIdx.x][tid * 8] = make_float4(cs[0], cs[1], cs[2], cs[3]);
        *(float4*)&g_cs[blockIdx.x][tid * 8 + 4] = make_float4(cs[4], cs[5], cs[6], cs[7]);
    }
}
constexpr int EARLY_A = 2, EARLY_B = 2;
__device__ __forceinline__ void reader_fence() { asm volatile("fence.proxy.async.global;" ::: "memory"); }

__device__ __forceinline__ bool poll_flags(const uint32_t* myflag, uint32_t target, uint32_t need, uint32_t& seen, int lane) {
    if ((seen & need) == need) return false;
    int spins = 0;
    while (true) {
        bool ready = (seen >> lane) & 1;
        if (!ready && myflag) ready = (int)(ld_acquire(myflag) - target) >= 0;
        seen = __ballot_sync(0xffffffffu, ready);
        if ((seen & need) == need) return true;
        if (++spins > (1 << 21)) __trap();
    }
}

__global__ void __launch_bounds__(NTHREADS, 1) fused_kernel(const __grid_constant__ Maps maps, const bf16* __restrict__ x, const bf16* __restrict__ wqkv,
                                                            const bf16* __restrict__ wo, const bf16* __restrict__ w1, const bf16* __restrict__ w2) {
    extern __shared__ __align__(1024) uint8_t smem[];
    const uint32_t sbase = smem_u32(smem);
    const int tid = threadIdx.x, warp_id = __shfl_sync(0xffffffffu, tid >> 5, 0), lane = tid & 31;
    Flags* const F = &g_flags;

    if (blockIdx.x < NHELP) {
        if (tid == 0) {
            for (int i = 0; i < PK_STAGES; i++) mbar_init(sbase + PK_BAR + 8 * i, 1);
            asm volatile("fence.mbarrier_init.release.cluster;" ::: "memory");
        }
        __syncthreads();
        int seq = 0;
        pack_weight<80, DM, 16, 0>(wo, g_wo_p, smem, sbase, seq, tid, nullptr);
        pack_weight<216, DM, 8, 1>(w1, g_w1_p, smem, sbase, seq, tid, nullptr);
        pack_weight<80, FF, 24, 2>(w2, g_w2_p, smem, sbase, seq, tid, F->pack[1]);
        if ((tid & 31) == 0) { asm volatile("cp.async.bulk.wait_group 0;" ::: "memory"); __threadfence(); }
        __syncthreads();
        if (tid == 0) flag_signal(F->pack[2]);
        return;
    }
    const int w = blockIdx.x - NHELP;
        const int mt = w >> 3, nt = w & 7;
    const int head = w >> 2, quarter = w & 3;
    if (warp_id >= 16 && elect_one()) {
        if (warp_id < 18) {
            const int r = warp_id - 16;
#pragma unroll
            for (int i = 0; i < ASLOTS; i++) mbar_init(sbase + BAR_FULLA + 8 * (r * ASLOTS + i), 1);
            asm volatile("fence.mbarrier_init.release.cluster;" ::: "memory");
#pragma unroll
            for (int i = 0; i < EARLY_A; i++) {
                mbar_expect(sbase + BAR_FULLA + 8 * (r * ASLOTS + i), 8192);
                tma_2d(sbase + OFF_A + r * A_RING + i * 8192, &maps.x, i * 64, (mt * 2 + r) * 64, sbase + BAR_FULLA + 8 * (r * ASLOTS + i));
            }
#pragma unroll
            for (int i = 0; i < ASLOTS; i++) mbar_init(sbase + BAR_EMPTYA + 8 * (r * ASLOTS + i), 16);
        } else if (warp_id == 18) {
#pragma unroll
            for (int i = 0; i < BSLOTS; i++) mbar_init(sbase + BAR_FULLB + 8 * i, 1);
            asm volatile("fence.mbarrier_init.release.cluster;" ::: "memory");
#pragma unroll
            for (int i = 0; i < EARLY_B; i++) {
                mbar_expect(sbase + BAR_FULLB + 8 * i, 32768);
#pragma unroll
                for (int b = 0; b < 4; b++) tma_3d(sbase + bslot_off(i) + b * 8192, &maps.wqkv, (b & 1) * 64, nt * 2, (i * 2 + (b >> 1)) * 64, sbase + BAR_FULLB + 8 * i);
            }
#pragma unroll
            for (int i = 0; i < BSLOTS; i++) mbar_init(sbase + BAR_EMPTYB + 8 * i, 16);
        } else {
            if (sbase & 1023) __trap();
#pragma unroll
            for (int i = 0; i < 16; i++) mbar_init(sbase + BAR_KV + 8 * i, 1);
        }
        asm volatile("fence.mbarrier_init.release.cluster;" ::: "memory");
    }
    if (warp_id == 0) { *(uint32_t*)(smem + OFF_ONES + lane * 4) = 0x3F803F80u; asm volatile("fence.proxy.async.shared::cta;" ::: "memory"); }
    if (warp_id == 1 && elect_one()) {
        mbar_init(sbase + BAR_KMAX, 4); *(uint2*)(smem + OFF_KMAX) = make_uint2(0u, 0u); mbar_init(sbase + BAR_AUX, 1); mbar_init(sbase + BAR_WQ, 1); mbar_init(sbase + BAR_DUMMY, 4);
#pragma unroll
        for (int i = 0; i < 5; i++) mbar_init(sbase + BAR_Q + 8 * i, 1);
        asm volatile("fence.mbarrier_init.release.cluster;" ::: "memory");
    }
    __syncthreads();

    if (warp_id >= 16) {
        auto load_kv = [&](int layer, int t0, int n, uint32_t epoch) {
            const uint8_t* gK = g_qkvx[layer] + (size_t)(NH + head) * HEAD_BYTES;
            const uint8_t* gV = g_qkvx[layer] + (size_t)(2 * NH + head) * HEAD_BYTES;
            const uint32_t* myflag = lane < 4 * n ? &F->qkv[((lane & 2 ? 2 * NH : NH) + head) / 6][(t0 + (lane >> 2)) * 2 + (lane & 1)] : nullptr;
            uint32_t seen = 0;
#pragma unroll 1
            for (int i = 0; i < n; i++) {
                const bool fresh = poll_flags(myflag, epoch * 2 - 1 + layer, 0xFu << (4 * i), seen, lane);
                if (fresh) reader_fence();
                if (elect_one()) {
                    const int t = t0 + i;
                    const uint32_t bar = sbase + BAR_KV + 8 * t;
                    mbar_expect(bar, 12288);
                    bulk_g2s(sbase + OFF_KV + t * 12288, gK + t * 6144, 6144, bar);
                    bulk_g2s(sbase + OFF_KV + t * 12288 + 6144, gV + t * 6144, 6144, bar);
                }
                __syncwarp();
            }
        };
        auto knorm = [&](int layer, int t0) {
            float km = 0.f;
#pragma unroll 1
            for (int t = t0; t < t0 + 4; t++) {
                mbar_wait_sleep(sbase + BAR_KV + 8 * t, layer);
#pragma unroll
                for (int u = 0; u < 4; u++) {
                    const int key = lane + u * 32;
                    const uint8_t* kp = smem + OFF_KV + t * 12288 + (key >> 3) * 384 + (key & 7) * 16;
                    const uint4 a = *(const uint4*)kp, b = *(const uint4*)(kp + 128);
                    const uint2 d = *(const uint2*)(kp + 256);
                    uint32_t e = hfma2(a.x, a.x, 0u), f = hfma2(a.y, a.y, 0u);
                    e = hfma2(a.z, a.z, e); f = hfma2(a.w, a.w, f); e = hfma2(b.x, b.x, e); f = hfma2(b.y, b.y, f);
                    e = hfma2(b.z, b.z, e); f = hfma2(b.w, b.w, f); e = hfma2(d.x, d.x, e); f = hfma2(d.y, d.y, f);
                    float n = (bf_lo(e) + bf_hi(e)) + (bf_lo(f) + bf_hi(f));
                    if ((POLY_MASK >> ((key >> 3) & 7)) & 1) n *= 0.25f;
                    km = n >= km ? n : (n != n ? INFINITY : km);
                }
            }
            const uint32_t kb = __reduce_max_sync(0xffffffffu, __float_as_uint(km));
            if (lane == 0) { atomicMax((uint32_t*)(smem + OFF_KMAX + layer * 4), kb); mbar_arrive(sbase + BAR_KMAX); }
            __syncwarp();
        };
        if (warp_id == 19) {
            float* cs_s = (float*)(smem + OFF_CS);
            const uint32_t epoch = __ldcg(F->epoch) + 1;
#pragma unroll 1
            for (int layer = 0; layer < 2; layer++) {
#pragma unroll 1
                for (int h = 0; h < 2; h++) {
                    NAMED_BAR(7 + h, 288);
                    if (lane < 2) flag_signal(&F->qkv[nt * 2 + h][mt * 2 + lane]);
                    __syncwarp();
                }
                knorm(layer, 4);
                if (layer == 0) {
                    flag_wait_warp<1000>(F->pack[1], epoch * NHELP);
                    for (int i = lane * 4; i < 216; i += 128) {
                        const float4 a = __ldcg((const float4*)&g_cs[0][nt * 216 + i]), b = __ldcg((const float4*)&g_cs[1][nt * 216 + i]);
                        const float4 c = __ldcg((const float4*)&g_cs[2][nt * 216 + i]), d = __ldcg((const float4*)&g_cs[3][nt * 216 + i]);
                        *(float4*)(cs_s + 240 + i) = make_float4((a.x + b.x) + (c.x + d.x), (a.y + b.y) + (c.y + d.y), (a.z + b.z) + (c.z + d.z), (a.w + b.w) + (c.w + d.w));
                    }
                    __syncwarp();
                    if (lane == 0) mbar_arrive(sbase + BAR_AUX);
                }
#pragma unroll 1
                for (int pass = 0; pass < 2; pass++) {
                    NAMED_BAR(14 + pass, 544);
                    if (lane < 4) flag_signal(&F->row[(quarter * 4 + lane) * 2 + pass][8 + layer]);
                    __syncwarp();
                }
            }
        } else if (warp_id == 18) {
            Ring rb = {EARLY_B, 1};
            auto stream = [&](const uint8_t* src, int total, int chunk) {
#pragma unroll 1
                for (int off = 0; off < total; off += chunk) {
                    const int n = total - off < chunk ? total - off : chunk;
                    if (total == 102400 || (total == 143360 && off == 0)) mbar_wait_sleep(sbase + BAR_EMPTYB + 8 * rb.slot, rb.phase);
                    else mbar_wait(sbase + BAR_EMPTYB + 8 * rb.slot, rb.phase);
                    __syncwarp();
                    if (elect_one()) {
                        mbar_expect(sbase + BAR_FULLB + 8 * rb.slot, n);
                        bulk_g2s(sbase + bslot_off(rb.slot), src + off, n, sbase + BAR_FULLB + 8 * rb.slot);
                    }
                    __syncwarp();
                    rb.next<BSLOTS>();
                }
            };
            uint32_t epoch = 0;
#pragma unroll 1
            for (int layer = 0; layer < 2; layer++) {
                if (layer == 1) {
                    flag_wait_warp<200>(F->pack[8 + nt], epoch * 16); reader_fence();
                    stream(g_wqkv_p + (size_t)nt * 307200, 153600, 30720);
                    stream(g_wqkv_p + (size_t)nt * 307200 + 153600 + 61440, 92160, 30720);
                    stream(g_wqkv_p + (size_t)nt * 307200 + 153600, 61440, 30720);
                } else
#pragma unroll 1
                for (int kb = EARLY_B; kb < 10; kb++) {
                    mbar_wait(sbase + BAR_EMPTYB + 8 * rb.slot, rb.phase);
                    __syncwarp();
                    if (elect_one()) {
                        mbar_expect(sbase + BAR_FULLB + 8 * rb.slot, 32768);
#pragma unroll
                        for (int b = 0; b < 4; b++) tma_3d(sbase + bslot_off(rb.slot) + b * 8192, &maps.wqkv, (b & 1) * 64, nt * 2 + (kb >= 5), ((kb < 5 ? kb : (kb - 3) % 5) * 2 + (b >> 1)) * 64, sbase + BAR_FULLB + 8 * rb.slot);
                    }
                    __syncwarp();
                    rb.next<BSLOTS>();
                }
                if (layer == 0) epoch = __ldcg(F->epoch) + 1;
#pragma unroll 1
                for (int i = 0; i < 3; i++) {
                    mbar_wait_sleep(sbase + BAR_EMPTYB + 8 * rb.slot, rb.phase);
                    __syncwarp();
                    if (lane == 0) mbar_arrive(sbase + BAR_FULLB + 8 * rb.slot);
                    rb.next<BSLOTS>();
                }
                __syncwarp();
                load_kv(layer, 0, 8, epoch);
                knorm(layer, 0);
                if (layer == 0) {
                    mbar_wait(sbase + BAR_EMPTYB + 8 * rb.slot, rb.phase);
                    __syncwarp();
                    if (elect_one()) { mbar_expect(sbase + BAR_WQ, 19200); tma_2d(sbase + bslot_off(rb.slot), &maps.wq_rows, nt * 240, mt * 40, sbase + BAR_WQ); }
                    __syncwarp();
                    mbar_wait_sleep(sbase + BAR_WQ, 0);
                    const uint8_t* src = smem + bslot_off(rb.slot) + (lane & 7) * 480;
                    uint8_t* dst = g_wqkv_p + (size_t)nt * 307200 + mt * 9600 + (lane & 7) * 16;
#pragma unroll 1
                    for (int kg = 0; kg < 5; kg++) {
#pragma unroll
                        for (int it = 0; it < 8; it++) {
                            const int ng = it * 4 + (lane >> 3);
                            if (ng < 30) *(uint4*)(dst + kg * 1920 + (ng < 15 ? ng * 128 : 153600 + (ng - 15) * 128)) = *(const uint4*)(src + kg * 3840 + ng * 16);
                        }
                    }
                    __syncwarp();
                    if (lane == 0) flag_signal(F->pack[8 + nt]);
                    __syncwarp();
                }
                if (layer == 0) { flag_wait_warp<500>(F->pack[1], epoch * NHELP); reader_fence(); }
                stream(g_wo_p + (size_t)nt * 102400, 102400, 30720);
                stream(g_w1_p + (size_t)nt * 276480, 143360, 28672);
                stream(g_w1_p + (size_t)nt * 276480 + 143360 + 53248, 79872, 26624);
                stream(g_w1_p + (size_t)nt * 276480 + 143360, 53248, 26624);
                if (layer == 0) { flag_wait_warp<200>(F->pack[2], epoch * NHELP); reader_fence(); }
                stream(g_w2_p + (size_t)nt * 276480, 276480, 30720);
            }
        } else {
            const int r = warp_id - 16, hb = mt * 2 + r;
            const uint32_t ring = sbase + OFF_A + r * A_RING, bfull = sbase + BAR_FULLA + 8 * r * ASLOTS, bempty = sbase + BAR_EMPTYA + 8 * r * ASLOTS;
            Ring ra = {EARLY_A, 1};
#pragma unroll 1
            for (int kb = EARLY_A; kb < 14; kb++) {
                mbar_wait(bempty + 8 * ra.slot, ra.phase);
                __syncwarp();
                if (elect_one()) {
                    mbar_expect(bfull + 8 * ra.slot, 8192);
                    tma_2d(ring + ra.slot * 8192, &maps.x, (kb % 10) * 64, hb * 64, bfull + 8 * ra.slot);
                }
                __syncwarp();
                ra.next<ASLOTS>();
            }
            const uint32_t epoch = __ldcg(F->epoch) + 1;
            auto stream_a = [&](const uint8_t* src, int KB, const uint32_t* flag, uint32_t target) {
                if (KB == 10) mbar_wait(bempty + 8 * ra.slot, ra.phase);
                __syncwarp();
                if (flag) { flag_wait_warp<0>(flag, target); reader_fence(); }
#pragma unroll 1
                for (int kb = 0; kb < KB; kb++) {
                    mbar_wait(bempty + 8 * ra.slot, ra.phase);
                    __syncwarp();
                    if (elect_one()) {
                        mbar_expect(bfull + 8 * ra.slot, 8192);
                        bulk_g2s(ring + ra.slot * 8192, src + kb * 8192, 8192, bfull + 8 * ra.slot);
                    }
                    __syncwarp();
                    ra.next<ASLOTS>();
                }
            };
#pragma unroll 1
            for (int layer = 0; layer < 2; layer++) {
                if (layer == 1) {
                    stream_a(g_xb + (size_t)hb * 81920, 10, &F->row[hb][1], epoch * 8);
                    stream_a(g_xb + (size_t)hb * 81920, 4, nullptr, 0);
                }
#pragma unroll 1
                for (int i = 0; i < ASLOTS; i++) {
                    mbar_wait(bempty + 8 * ra.slot, ra.phase);
                    __syncwarp();
                    if (lane == 0) mbar_arrive(bfull + 8 * ra.slot);
                    ra.next<ASLOTS>();
                }
                __syncwarp();
                {
                    uint32_t seen = 0, told = 0;
                    const uint32_t* qf = lane < 4 ? &F->qkv[head / 6][(quarter * 4 + lane) * 2 + r] : nullptr;
                    if (r == 0) {
                        int spins = 0;
                        while (told != 0xFu) {
                            const bool ready = lane < 4 && (((told >> lane) & 1) || (int)(ld_acquire(qf) - (epoch * 2 - 1 + layer)) >= 0);
                            if (ready && !((told >> lane) & 1)) mbar_arrive(sbase + BAR_Q + 8 * lane);
                            told = __ballot_sync(0xffffffffu, ready);
                            if (++spins > (1 << 21)) __trap();
                        }
                    } else {
                        poll_flags(qf, epoch * 2 - 1 + layer, 0xFu, seen, lane);
                        if (lane == 0) mbar_arrive(sbase + BAR_Q + 32);
                    }
                }
                load_kv(layer, 8 + 4 * r, 4, epoch);
                knorm(layer, 8 + 4 * r);
                mbar_wait_sleep(bempty + 8 * ra.slot, ra.phase);
                __syncwarp();
                stream_a(g_o + (size_t)hb * 81920, 10, &F->row[hb][8 + layer], epoch * 32);
                stream_a(g_xa + (size_t)hb * 81920, 10, &F->row[hb][layer * 2], epoch * 8);
                stream_a(g_xa + (size_t)hb * 81920, 4, nullptr, 0);
                stream_a(g_h + (size_t)hb * 221184, 14, &F->row[hb][4 + layer * 2], epoch * 8);
                stream_a(g_h + (size_t)hb * 221184 + 114688, 13, &F->row[hb][5 + layer * 2], epoch * 8);
            }
            if (w == 0 && r == 0 && lane == 0) *(volatile uint32_t*)F->epoch = epoch;
        }
    } else {
        const int wg = warp_id >> 2, warp = warp_id & 3;
        const int r = wg & 1, h = wg >> 1, hb = mt * 2 + r;
        float* cs_s = (float*)(smem + OFF_CS);
        const uint32_t ring = sbase + OFF_A + r * A_RING;
#pragma unroll 1
        for (int layer = 0; layer < 2; layer++) {
            {
                float acc[60];
                float2 st0, st1;
                if (layer == 0) {
                    float csum[4] = {0.f, 0.f, 0.f, 0.f};
                    fence_regs(csum);
                    float4 sq = make_float4(0.f, 0.f, 0.f, 0.f);
                    THREAD_IDS;
                    const uint8_t* tp0 = smem + OFF_A + r * A_RING + lrow * 128 + (c << 4);
                    seg_loop<120, 2, true>(acc, csum, 0, 10, sbase, r, h * 4, h * 5, mkdesc(sbase, 8192, 1024, 1), 10, h ? 0 : 4, h ? 6 : 10, 2, 2, h ? 9 + r : 0, 9 + r, h ? -1 : 8, lane,
                        [&](uint32_t as8) {
                            if (h == 0) {
#pragma unroll
                                for (int u = 0; u < 2; u++) {
                                    const uint8_t* tp = tp0 + as8 * 1024 + (((g & 1) ^ u) << 6);
                                    const uint4 x0 = *(const uint4*)tp, x1 = *(const uint4*)(tp + 1024);
                                    const uint32_t a[4] = {x0.x, x0.y, x0.z, x0.w}, b[4] = {x1.x, x1.y, x1.z, x1.w};
#pragma unroll
                                    for (int e = 0; e < 4; e++) {
                                        const float a0 = bf_lo(a[e]), a1 = bf_hi(a[e]), b0 = bf_lo(b[e]), b1 = bf_hi(b[e]);
                                        sq.x += a0 + a1; sq.y = fmaf(a0, a0, sq.y); sq.y = fmaf(a1, a1, sq.y);
                                        sq.z += b0 + b1; sq.w = fmaf(b0, b0, sq.w); sq.w = fmaf(b1, b1, sq.w);
                                    }
                                }
                            }
                        });
                    if (c == 0) {
                        cs_s[h * 120 + r * 64 + lrow] = csum[0];
                        if (r * 64 + lrow + 8 < 120) cs_s[h * 120 + r * 64 + lrow + 8] = csum[2];
                    }
                    float2* sts = (float2*)(smem + OFF_ST0) + r * 64 + lrow;
                    if (h == 0) {
                        st0 = StatRegs::fin(make_float4(sq.x, sq.y, 0.f, 0.f), make_float4(0.f, 0.f, 0.f, 0.f));
                        st1 = StatRegs::fin(make_float4(sq.z, sq.w, 0.f, 0.f), make_float4(0.f, 0.f, 0.f, 0.f));
                        if (c == 0) { sts[0] = st0; sts[8] = st1; }
                        asm volatile("bar.arrive %0, 256;" :: "r"(1 + r) : "memory");
                        NAMED_BAR(13, 256);
                    } else {
                        NAMED_BAR(1 + r, 256);
                        st0 = sts[0]; st1 = sts[8];
                        NAMED_BAR(12, 256);
                    }
                } else {
                    float nocs[4];
                    StatRegs sv; sv.clear();
                    THREAD_IDS;
                    seg_loop<120, 2, false>(acc, nocs, 0, 10, sbase, r, A_PER_LAYER + h * 4, B_PER_LAYER + h * 5, mkdesc(sbase, 1920, 128, 0), 10, h ? 0 : 4, h ? 6 : 10, 2, 2, h ? 9 + r : 0, 9 + r, h ? -1 : 8, lane,
                        [&](int kb) { if (kb == 0) sv.load(&g_stats[2][hb][0][0], lrow, c); if (kb == 6) sv.finish(); });
                    st0 = sv.st0; st1 = sv.st1;
                }
                THREAD_IDS;
                const float2* cs = (const float2*)(cs_s + h * 120) + c;
                const int rg = (tid >> 4) & 6, gh0 = nt * 12 + (tid >> 8) * 6;
                const bool poly0 = (POLY_MASK >> rg) & 1, poly1 = (POLY_MASK >> (rg + 1)) & 1, lo = c < 2;
                uint32_t* oe = (uint32_t*)(g_qkvx[layer] + (size_t)gh0 * HEAD_BYTES + hb * 3072 + rg * 384 + g * 16) + c;
                uint32_t* oo = oe + (HEAD_BYTES / 4) + (c ^ 2) - c;
#pragma unroll
                for (int p = 0; p < 3; p++) {
                    const int which = (gh0 + p * 2) >> 5;
                    const float f0 = which == 0 ? 0.32259642f : (which == 1 && poly0 ? 2.f : 1.f);
                    const float f1 = which == 0 ? 0.32259642f : (which == 1 && poly1 ? 2.f : 1.f);
                    const float a0 = st0.x * f0, b0 = st0.y * f0, a1 = st1.x * f1, b1 = st1.y * f1;
                    const uint32_t pq = (c & 1) ? 0x00003F80u : 0x3F803F80u, pk = (c & 1) ? 0x0000BB88u : 0xC04B4440u, pv = (c & 1) ? 0u : 0x00003F80u;
                    const uint32_t pad0 = which == 0 ? pq : (which == 1 ? (poly0 ? pk : 0u) : pv), pad1 = which == 0 ? pq : (which == 1 ? (poly1 ? pk : 0u) : pv);
                    uint32_t v0[5], v1[5];
#pragma unroll
                    for (int jj = 0; jj < 5; jj++) {
                        const int j = p * 5 + jj;
                        const float2 cv = cs[j * 4];
                        v0[jj] = pack_bf16(fmaf(acc[4 * j], a0, b0 * cv.x), fmaf(acc[4 * j + 1], a0, b0 * cv.y));
                        v1[jj] = pack_bf16(fmaf(acc[4 * j + 2], a1, b1 * cv.x), fmaf(acc[4 * j + 3], a1, b1 * cv.y));
                    }
                    uint32_t* e = oe + p * (HEAD_BYTES / 2);
                    uint32_t* o = oo + p * (HEAD_BYTES / 2);
                    e[0] = v0[0]; e[96] = v1[0]; e[32] = v0[1]; e[128] = v1[1];
                    e[64] = lo ? v0[2] : pad0; e[160] = lo ? v1[2] : pad1;
                    o[0] = lo ? v0[3] : v0[2]; o[96] = lo ? v1[3] : v1[2];
                    o[32] = lo ? v0[4] : v0[3]; o[128] = lo ? v1[4] : v1[3];
                    o[64] = lo ? pad0 : v0[4]; o[160] = lo ? pad1 : v1[4];
                }
                asm volatile("bar.arrive %0, 288;" :: "r"(7 + h) : "memory");
            }
            {
                const uint64_t dK0 = mkdesc(sbase + OFF_KV, 128, 384, 0), dK1 = mkdesc(sbase + OFF_KV + 256, 0, 384, 0), dV = mkdesc(sbase + OFF_KV + 6144, 384, 128, 0);
                const uint32_t* gq0 = (const uint32_t*)(g_qkvx[layer] + (size_t)head * HEAD_BYTES + (quarter * 4 + wg) * 6144 + warp * 768);
                mbar_wait(sbase + BAR_Q + 8 * wg, layer);
                uint32_t q0, q1, q2, q3, q4, q5;
                {
                    THREAD_IDS;
                    const uint32_t* gq = gq0 + lane;
                    q0 = __ldcg(gq); q1 = __ldcg(gq + 96); q2 = __ldcg(gq + 32); q3 = __ldcg(gq + 128); q4 = __ldcg(gq + 64); q5 = __ldcg(gq + 160);
                }
#pragma unroll 1
                for (int pass = 0; pass < 2; pass++) {
                    const int hbq = (quarter * 4 + wg) * 2 + pass;
                    uint32_t zero = 0, mmask = 0x007F007Fu;
                    asm volatile("" : "+r"(zero), "+r"(mmask));
                    float o[12], s0[32];
                    uint32_t p0[16];
#pragma unroll
                    for (int i = 0; i < 12; i++) o[i] = 0.f;
#pragma unroll
                    for (int i = 0; i < 32; i++) s0[i] = 0.f;
#pragma unroll
                    for (int i = 0; i < 16; i++) p0[i] = 0u;
                    fence_regs(o); fence_regs(s0); fence_regs(p0);
#pragma unroll 1
                    for (int t = 0; t < 16; t++) {
                        const uint32_t cur = t * (12288 >> 4);
                        const uint32_t vprev = t > 0 ? cur - ((12288 - 3072) >> 4) : 0;
                        if (pass == 0) mbar_wait(sbase + BAR_KV + 8 * t, layer);
                        WG_FENCE();
                        ATT_PV(vprev);
                        ATT_QK(cur);
                        WG_COMMIT();
                        WG_WAIT(0);
                        if (pass == 1 && ((0x1148u >> t) & 1)) {
                            THREAD_IDS;
                            if (t == 12) { if (lane < ASLOTS) mbar_arrive(sbase + BAR_EMPTYA + 8 * lane); }
                            else if (lane == 0) mbar_arrive(sbase + BAR_EMPTYB + 8 * (t == 3 ? 2 : (t == 6 ? 3 : 0)));
                        }
                        exp_tile(s0, p0, mmask);
                        WG_FENCE();
                        ATT_PV(cur);
                        ATT_QK(cur + (3072 >> 4));
                        WG_COMMIT();
                        WG_WAIT(0);
                        exp_tile(s0, p0, mmask);
                    }
                    WG_FENCE();
                    ATT_PV((15 * 12288 + 3072) >> 4);
                    WG_COMMIT();
                    THREAD_IDS;
                    const uint32_t* gq = gq0 + lane;
                    const uint32_t q4m = c < 2 ? q4 : 0u, q5m = c < 2 ? q5 : 0u;
                    float n0 = bf_lo(q0) * bf_lo(q0) + bf_hi(q0) * bf_hi(q0) + bf_lo(q2) * bf_lo(q2) + bf_hi(q2) * bf_hi(q2) + bf_lo(q4m) * bf_lo(q4m) + bf_hi(q4m) * bf_hi(q4m);
                    float n1 = bf_lo(q1) * bf_lo(q1) + bf_hi(q1) * bf_hi(q1) + bf_lo(q3) * bf_lo(q3) + bf_hi(q3) * bf_hi(q3) + bf_lo(q5m) * bf_lo(q5m) + bf_hi(q5m) * bf_hi(q5m);
                    if (pass == 0) { mbar_wait(sbase + BAR_Q + 32, layer); q0 = __ldcg(gq + 768); q1 = __ldcg(gq + 768 + 96); q2 = __ldcg(gq + 768 + 32); q3 = __ldcg(gq + 768 + 128); q4 = __ldcg(gq + 768 + 64); q5 = __ldcg(gq + 768 + 160); }
                    n0 += __shfl_xor_sync(0xffffffffu, n0, 1); n0 += __shfl_xor_sync(0xffffffffu, n0, 2);
                    n1 += __shfl_xor_sync(0xffffffffu, n1, 1); n1 += __shfl_xor_sync(0xffffffffu, n1, 2);
                    mbar_wait(sbase + BAR_KMAX, layer);
                    const float kmax = *(volatile float*)(smem + OFF_KMAX + layer * 4) * 1.1f;
                    bool ok = n0 * kmax <= 9800.f && n1 * kmax <= 9800.f;
                    WG_WAIT(0);
                    fence_regs(o);
                    if (pass == 1 && lane < ASLOTS) mbar_arrive(sbase + BAR_EMPTYA + 8 * ASLOTS + 8 * lane);
#pragma unroll
                    for (int i = 0; i < 12; i++) ok = ok && fabsf(o[i]) < 1e30f;
                    if (c == 2) ok = ok && o[8] > 1e-6f && o[10] > 1e-6f;
                    if (!__all_sync(0xffffffffu, ok)) attn_rows_safe(o, gq + pass * 768, g_qkvx[layer], head, lane);
                    const float l0 = __shfl_sync(0xffffffffu, o[8], (lane & ~3) | 2), l1 = __shfl_sync(0xffffffffu, o[10], (lane & ~3) | 2);
                    const float r0 = __fdividef(1.f, l0), r1 = __fdividef(1.f, l1);
                    const int col = head * DH + 2 * c;
                    uint8_t* ob = g_o + (size_t)hbq * 81920 + (col >> 3) * 1024 + lrow * 16 + (col & 7) * 2;
                    *(uint32_t*)ob = pack_bf16(o[0] * r0, o[1] * r0); *(uint32_t*)(ob + 128) = pack_bf16(o[2] * r1, o[3] * r1);
                    *(uint32_t*)(ob + 1024) = pack_bf16(o[4] * r0, o[5] * r0); *(uint32_t*)(ob + 1024 + 128) = pack_bf16(o[6] * r1, o[7] * r1);
                    if (c < 2) { *(uint32_t*)(ob + 2048) = pack_bf16(o[8] * r0, o[9] * r0); *(uint32_t*)(ob + 2048 + 128) = pack_bf16(o[10] * r1, o[11] * r1); }
                    asm volatile("bar.arrive %0, 544;" :: "r"(14 + pass) : "memory");
                }
            }
#pragma unroll 1
            for (int ph = 0; ph < 2; ph++) {
                {
                    uint32_t res[10];
                    float acc[40];
                    { THREAD_IDS;
                    if (layer == 0 && ph == 0) {
                        const uint32_t* r0 = (const uint32_t*)(x + (size_t)(hb * 64 + lrow) * DM + nt * 80 + h * 40) + c;
#pragma unroll
                        for (int j = 0; j < 5; j++) { res[2 * j] = __ldg(r0 + j * 4); res[2 * j + 1] = __ldg(r0 + j * 4 + 8 * DM / 2); }
                    } else {
                        const uint32_t* r0 = (const uint32_t*)((ph == 1 ? g_xa : g_xb) + (size_t)hb * 81920 + nt * 10240 + h * 5120 + lrow * 16) + c;
#pragma unroll
                        for (int j = 0; j < 5; j++) { res[2 * j] = __ldcg(r0 + j * 256); res[2 * j + 1] = __ldcg(r0 + j * 256 + 32); }
                    }
                    if (ph == 0) wo_loop(acc, sbase, r, h, layer * A_PER_LAYER + 20, layer * B_PER_LAYER + 13, lane);
                    else {
                        float nocs[4];
                        seg_loop<80, 3, false>(acc, nocs, h * 2, 14 + h, sbase, r, layer * A_PER_LAYER + 44 + h * 14, layer * B_PER_LAYER + 27 + h * 4, mkdesc(sbase, 1280, 128, 0),
                                        h == 0 ? 14 : 15 - ASLOTS, 0, 0, 2 - h, 1 + h, (h == 0 ? 11 : 9) + r, 9 + r, h == 0 ? 13 : -1, lane, [&](int) {});
                    }
                    }
                    THREAD_IDS;
                    NAMED_BAR(1 + r, 256);
                    float4* xs = (float4*)(smem + OFF_A + r * A_RING + 20480);
#pragma unroll
                    for (int j = 0; j < 5; j++)
                        xs[(h * 5 + j) * 128 + t128] = h == 0 ? make_float4(acc[20 + 4 * j], acc[21 + 4 * j], acc[22 + 4 * j], acc[23 + 4 * j])
                                                              : make_float4(acc[4 * j], acc[4 * j + 1], acc[4 * j + 2], acc[4 * j + 3]);
                    NAMED_BAR(1 + r, 256);
                    uint32_t ov[10];
                    float s0 = 0.f, s1 = 0.f, q0 = 0.f, q1 = 0.f;
#pragma unroll
                    for (int j = 0; j < 5; j++) {
                        const float4 u = xs[((1 - h) * 5 + j) * 128 + t128];
                        const float m0 = h == 0 ? acc[4 * j] : acc[20 + 4 * j], m1 = h == 0 ? acc[4 * j + 1] : acc[21 + 4 * j];
                        const float m2 = h == 0 ? acc[4 * j + 2] : acc[22 + 4 * j], m3 = h == 0 ? acc[4 * j + 3] : acc[23 + 4 * j];
                        ov[2 * j] = pack_bf16(m0 + u.x + bf_lo(res[2 * j]), m1 + u.y + bf_hi(res[2 * j]));
                        ov[2 * j + 1] = pack_bf16(m2 + u.z + bf_lo(res[2 * j + 1]), m3 + u.w + bf_hi(res[2 * j + 1]));
                        const float a = bf_lo(ov[2 * j]), b = bf_hi(ov[2 * j]), d = bf_lo(ov[2 * j + 1]), e = bf_hi(ov[2 * j + 1]);
                        s0 += a + b; q0 = fmaf(a, a, q0); q0 = fmaf(b, b, q0);
                        s1 += d + e; q1 = fmaf(d, d, q1); q1 = fmaf(e, e, q1);
                    }
                    const bool last = layer == 1 && ph == 1;
                    if (last) {
                        stage_tile_swz<5>(ov, ring, h * 5, warp, lane);
                        asm volatile("fence.proxy.async.shared::cta;" ::: "memory");
                        NAMED_BAR(1 + r, 256);
                        if (t128 == 0 && h == 0) {
                            tma_store_3d(&maps.st_out, ring, 0, nt, hb * 64);
                            tma_store_3d(&maps.st_out, ring + 8192, 64, nt, hb * 64);
                            bulk_commit_wait();
                        }
                    } else {
                        uint32_t* out = (uint32_t*)((ph == 0 ? g_xa : g_xb) + (size_t)hb * 81920 + nt * 10240 + h * 5120 + lrow * 16) + c;
#pragma unroll
                        for (int j = 0; j < 5; j++) { out[j * 256] = ov[2 * j]; out[j * 256 + 32] = ov[2 * j + 1]; }
                        s0 += __shfl_xor_sync(0xffffffffu, s0, 1); q0 += __shfl_xor_sync(0xffffffffu, q0, 1);
                        s1 += __shfl_xor_sync(0xffffffffu, s1, 1); q1 += __shfl_xor_sync(0xffffffffu, q1, 1);
                        s0 += __shfl_xor_sync(0xffffffffu, s0, 2); q0 += __shfl_xor_sync(0xffffffffu, q0, 2);
                        s1 += __shfl_xor_sync(0xffffffffu, s1, 2); q1 += __shfl_xor_sync(0xffffffffu, q1, 2);
                        float2* so = (float2*)&g_stats[layer * 2 + 1 + ph][hb][nt][lrow] + h;
                        if (c == 0) { so[0] = make_float2(s0, q0); so[16] = make_float2(s1, q1); }
                        NAMED_BAR(1 + r, 256);
                        if (t128 == 0) {
                            if (h == 0) release_ring(sbase, r, 16);
                            else flag_signal(&F->row[hb][layer * 2 + ph]);
                        }
                    }
                    __syncwarp();
                }
                if (ph == 0) {
                    const float4* stats = &g_stats[layer * 2 + 1][hb][0][0];
                    uint8_t* hdst = g_h + (size_t)hb * 221184 + (h == 0 ? nt * 14336 : 114688 + nt * 13312);
                    if (h == 0) w1_phase<112>(sbase, cs_s, r, 0, layer * A_PER_LAYER + 30, layer * B_PER_LAYER + 17, stats, warp, hdst);
                    else w1_phase<104>(sbase, cs_s, r, 14, layer * A_PER_LAYER + 34, layer * B_PER_LAYER + 22, stats, warp, hdst);
                    NAMED_BAR(3 + wg, 128);
                    THREAD_IDS;
                    if (t128 == 0) flag_signal(&F->row[hb][4 + layer * 2 + h]);
                    __syncwarp();
                }
            }
        }
    }
}

typedef CUresult (*EncodeFn)(CUtensorMap*, CUtensorMapDataType, cuuint32_t, void*, const cuuint64_t*, const cuuint64_t*, const cuuint32_t*,
                             const cuuint32_t*, CUtensorMapInterleave, CUtensorMapSwizzle, CUtensorMapL2promotion, CUtensorMapFloatOOBfill);
static EncodeFn s_encode;
static CUtensorMap map2d(const void* p, int rows, int cols) {
    CUtensorMap m;
    cuuint64_t dims[2] = {(cuuint64_t)cols, (cuuint64_t)rows}, strides[1] = {(cuuint64_t)cols * 2};
    cuuint32_t box[2] = {64, 64}, es[2] = {1, 1};
    s_encode(&m, CU_TENSOR_MAP_DATA_TYPE_BFLOAT16, 2, (void*)p, dims, strides, box, es, CU_TENSOR_MAP_INTERLEAVE_NONE, CU_TENSOR_MAP_SWIZZLE_128B,
             CU_TENSOR_MAP_L2_PROMOTION_L2_128B, CU_TENSOR_MAP_FLOAT_OOB_FILL_NONE);
    return m;
}
static CUtensorMap map3d(const void* p, int rows, int bn, int nt) {
    CUtensorMap m;
    cuuint64_t dims[3] = {(cuuint64_t)bn, (cuuint64_t)nt, (cuuint64_t)rows}, strides[2] = {(cuuint64_t)bn * 2, (cuuint64_t)bn * nt * 2};
    cuuint32_t box[3] = {64, 1, 64}, es[3] = {1, 1, 1};
    s_encode(&m, CU_TENSOR_MAP_DATA_TYPE_BFLOAT16, 3, (void*)p, dims, strides, box, es, CU_TENSOR_MAP_INTERLEAVE_NONE, CU_TENSOR_MAP_SWIZZLE_128B,
             CU_TENSOR_MAP_L2_PROMOTION_L2_128B, CU_TENSOR_MAP_FLOAT_OOB_FILL_NONE);
    return m;
}

extern "C" void kernel_launch(void* const* d_in, const int* in_sizes, int n_in, void* d_out, int out_size) {
    const bf16* x = (const bf16*)d_in[0];
    const bf16* wqkv = (const bf16*)d_in[1];
    const bf16* wo = (const bf16*)d_in[2];
    const bf16* w1 = (const bf16*)d_in[4];
    const bf16* w2 = (const bf16*)d_in[5];
    if (!s_encode) {
        cudaDriverEntryPointQueryResult qr;
        void* fn = nullptr;
        cudaGetDriverEntryPoint("cuTensorMapEncodeTiled", &fn, cudaEnableDefault, &qr);
        s_encode = (EncodeFn)fn;
        cudaFuncSetAttribute(fused_kernel, cudaFuncAttributeMaxDynamicSharedMemorySize, SMEM_BYTES);
    }
    Maps m;
    m.x = map2d(x, SEQ, DM);
    m.wqkv = map3d(wqkv, DM, 120, 16);
    m.st_out = map3d(d_out, SEQ, 80, 8);
    {
        cuuint64_t dims[2] = {3 * DM, DM}, strides[1] = {3 * DM * 2};
        cuuint32_t box[2] = {240, 40}, es[2] = {1, 1};
        s_encode(&m.wq_rows, CU_TENSOR_MAP_DATA_TYPE_BFLOAT16, 2, (void*)wqkv, dims, strides, box, es, CU_TENSOR_MAP_INTERLEAVE_NONE, CU_TENSOR_MAP_SWIZZLE_NONE,
                 CU_TENSOR_MAP_L2_PROMOTION_L2_128B, CU_TENSOR_MAP_FLOAT_OOB_FILL_NONE);
    }
    fused_kernel<<<NHELP + NWORK, NTHREADS, SMEM_BYTES, cudaStreamPerThread>>>(m, x, wqkv, wo, w1, w2);
}
```
